```python
import torch

def _softmax(x, axis=-1):
    return torch.softmax(x, dim=axis)

def _gelu(x):
    return torch.nn.functional.gelu(x, approximate='tanh')

def _silu(x):
    return torch.nn.functional.silu(x)

def _sigmoid(x):
    return torch.sigmoid(x)

def _layernorm(x, axis=-1, eps=1e-05):
    m = x.mean(dim=axis, keepdim=True)
    v = x.var(dim=axis, keepdim=True, unbiased=False)
    return (x - m) / torch.sqrt(v + eps)

def _scatter_add(tgt, idx, src, axis=0):
    return tgt.clone().index_add_(axis, idx, src)

def _segment_sum(src, seg, n):
    out = torch.zeros((n,) + src.shape[1:], dtype=src.dtype)
    return out.index_add_(0, seg, src)

def _pad(x, pw):
    flat = tuple((v for pair in reversed(pw) for v in pair))
    return torch.nn.functional.pad(x, flat)
kernel_name = 'adaLN_cond__ssm_conv_s4__mixer_s_mlp__prompt'

def setup_inputs():

    _w = lambda a: (lambda t: t.to(torch.bfloat16) if t.is_floating_point() else t)(torch.as_tensor(a))

    def _A_setup():
        B, L, D, N = (1, 2048, 512, 128)
        A_re = -(lambda _x: torch.exp(torch.as_tensor(_x)))((lambda *s: torch.randn(*s, dtype=torch.bfloat16) * 3.2)(D, N))
        A_im = torch.pi * (lambda *s: torch.randn(*s, dtype=torch.bfloat16) * 0.1)(D, N)
        B_re = (lambda *s: torch.randn(*s, dtype=torch.bfloat16) * 0.2)(D, N)
        B_im = (lambda *s: torch.randn(*s, dtype=torch.bfloat16) * 0.2)(D, N)
        C_re = (lambda *s: torch.randn(*s, dtype=torch.bfloat16) * 0.2)(D, N)
        C_im = (lambda *s: torch.randn(*s, dtype=torch.bfloat16) * 0.2)(D, N)
        log_dt = (lambda *s: torch.randn(*s, dtype=torch.bfloat16) * 0.1)(D) * 0.5 - 4.0
        Dskip = (lambda *s: torch.randn(*s, dtype=torch.bfloat16) * 0.1)(D)
        return {'u': _w((lambda *s: torch.randn(*s, dtype=torch.bfloat16) * 0.05)(B, L, D)), 'A_re': _w(A_re), 'A_im': _w(A_im), 'B_re': _w(B_re), 'B_im': _w(B_im), 'C_re': _w(C_re), 'C_im': _w(C_im), 'log_dt': _w(log_dt), 'Dskip': _w(Dskip)}
    _A_in = _A_setup()

    def _B_setup():
        B, S, D, F = (1, 2048, 512, 1792)
        return {'x': _w((lambda *s: torch.randn(*s, dtype=torch.bfloat16) * 0.05)(B, S, D)), 'w1': _w((lambda *s: torch.randn(*s, dtype=torch.bfloat16) * 3.2)(D, D) * D ** (-0.5)), 'w2': _w((lambda *s: torch.randn(*s, dtype=torch.bfloat16) * 3.2)(D, D) * D ** (-0.5)), 'w3': _w((lambda *s: torch.randn(*s, dtype=torch.bfloat16) * 3.2)(D, F) * D ** (-0.5)), 'w4': _w((lambda *s: torch.randn(*s, dtype=torch.bfloat16) * 1.6)(F, D) * F ** (-0.5))}
    _B_in = _B_setup()
    return {'A_u': _A_in['u'], 'A_A_re': _A_in['A_re'], 'A_A_im': _A_in['A_im'], 'A_B_re': _A_in['B_re'], 'A_B_im': _A_in['B_im'], 'A_C_re': _A_in['C_re'], 'A_C_im': _A_in['C_im'], 'A_log_dt': _A_in['log_dt'], 'A_Dskip': _A_in['Dskip'], 'B_x': _B_in['x'], 'B_w1': _B_in['w1'], 'B_w2': _B_in['w2'], 'B_w3': _B_in['w3'], 'B_w4': _B_in['w4'], 'c': _w((lambda *s: torch.randn(*s, dtype=torch.bfloat16) * 0.1)(1, 512) * 8.0), 'w_mod': _w((lambda *s: torch.randn(*s, dtype=torch.bfloat16) * 0.1)(512, 6 * 512) * 512 ** (-0.5) * 8.0)}

def reference(A_u, A_A_re, A_A_im, A_B_re, A_B_im, A_C_re, A_C_im, A_log_dt, A_Dskip, B_x, B_w1, B_w2, B_w3, B_w4, c, w_mod):

    def _A_ref(u, A_re, A_im, B_re, B_im, C_re, C_im, log_dt, Dskip):
        Bsz, L, D = u.shape
        dt = torch.exp(log_dt)[:, None]
        A = A_re + 1j * A_im
        Bc = B_re + 1j * B_im
        Cc = C_re + 1j * C_im
        logdA = dt * A
        dB = dt * Bc
        l = (lambda x, dt: x.to(dt))(torch.arange(L), A_re.dtype)
        P = torch.exp(logdA[:, :, None] * l[None, None, :])
        K = torch.einsum('dn,dnl,dn->dl', Cc, P, dB).real
        L2 = 2 * L
        Kp = _pad(K, ((0, 0), (0, L)))
        up = (lambda x, *d: x.permute(*d))(u, 0, 2, 1)
        up = _pad(up, ((0, 0), (0, 0), (0, L)))
        Kf = (lambda x, axes=(-2, -1): torch.fft.rfft2(x.float(), dim=axes))(Kp[:, None, :], axes=(-2, -1))
        Uf = (lambda x, axes=(-2, -1): torch.fft.rfft2(x.float(), dim=axes))(up[:, :, None, :], axes=(-2, -1))
        Yf = Uf * Kf[None, :, :, :]
        y = (lambda x, s, axes=(-2, -1): torch.fft.irfft2(x, s=s, dim=axes).to(torch.bfloat16))(Yf, (1, L2), axes=(-2, -1))[:, :, 0, :L]
        y = (lambda x, *d: x.permute(*d))(y, 0, 2, 1) + u * Dskip[None, None, :]
        return y

    def _B_ref(x, w1, w2, w3, w4):
        B, S, D = x.shape
        h = _gelu(_layernorm(x, axis=-1) @ w1)
        c = D // 4
        g0 = _pad(h[:, :, 0 * c:1 * c], ((0, 0), (1, 0), (0, 0)))[:, :S, :]
        g1 = _pad(h[:, :, 1 * c:2 * c], ((0, 0), (0, 1), (0, 0)))[:, 1:, :]
        g2 = _pad(h[:, :, 2 * c:3 * c], ((0, 0), (2, 0), (0, 0)))[:, :S, :]
        g3 = _pad(h[:, :, 3 * c:], ((0, 0), (0, 2), (0, 0)))[:, 2:, :]
        hs = torch.concatenate([g0, g1, g2, g3], axis=-1) @ w2
        x1 = x + hs
        h2 = _gelu(_layernorm(x1, axis=-1) @ w3) @ w4
        return x1 + h2
    x = A_u
    mod = (_silu(c) @ w_mod).reshape(c.shape[0], 6, 1, -1)
    sa, ca, ga, sb, cb, gb = (mod[:, 0].clone(), mod[:, 1].clone(), mod[:, 2].clone(), mod[:, 3].clone(), mod[:, 4].clone(), mod[:, 5].clone())
    h = _layernorm(x, axis=-1) * (1 + ca) + sa
    x = x + ga * _A_ref(h, A_A_re, A_A_im, A_B_re, A_B_im, A_C_re, A_C_im, A_log_dt, A_Dskip)
    h = _layernorm(x, axis=-1) * (1 + cb) + sb
    x = x + gb * _B_ref(h, B_w1, B_w2, B_w3, B_w4)
    return x
```

```cpp
#include <cuda_runtime.h>
#include <cuda_bf16.h>
#include <cuda.h>
#include <stdint.h>
#include <stddef.h>

typedef __nv_bfloat16 bf16;
typedef unsigned long long u64;

struct Scratch {
    bf16     h[2052 * 512];
    uint4    z[32 * 8 * 512];
    uint4    part[128 * 3 * 1024];
    uint2    x1[128 * 2048];
    float2   zst[32 * 8 * 64];
    unsigned stats[2048];
    unsigned modp[8 * 3072];
    unsigned csum[8 * 2304];
    bf16     modf[3 * 512];
    unsigned f0[2 * 8 * 32], fh[32 * 32], fz[32 * 32], fp[128 * 32], epoch[128 * 32];
};
__device__ __align__(1024) Scratch g_s;
#define TS(i)

struct Params {
    const bf16* par[8];
    const bf16 *x, *wmod, *c;
    Scratch* s;
    const bf16 *w1, *w2, *w3, *w4;
    bf16* out;
};
struct Maps { CUtensorMap m[9]; };
#define tmX M.m[0]
#define tmW1 M.m[1]
#define tmW2 M.m[2]
#define tmW3 M.m[3]
#define tmW3b M.m[4]
#define tmW4 M.m[5]
#define tmW4h M.m[6]
#define tmH M.m[7]
#define tmX1 M.m[8]

constexpr uint32_t SLOT = 16384;
constexpr uint32_t KST_P = 272, KST_W = 53 * 272, KP_P = 112;
constexpr uint32_t FT_CH = 3520, O_FT = 8 * SLOT - 4 * FT_CH;
constexpr uint32_t O_BOX = 8 * SLOT, BOX_CH = 12928, B5_O = 0, B3_O = 3200, B9_O = 6400, B7_O = 8576, B2_O = 10752;
constexpr uint32_t H2O = 1600, H3O = 1088;
constexpr uint32_t O_XG = O_BOX;
constexpr uint32_t O_U = O_BOX + 4 * BOX_CH, U_CH = 4480, U_H = 2240;
constexpr uint32_t O_NT = O_U + 4 * U_CH, NT_CH = 4496, NT_R = 280, NT_B = 2252;
constexpr uint32_t O_Y0 = O_NT + 4 * NT_CH, Y_CH = 2112;
constexpr uint32_t O_WS = O_Y0 + 4 * Y_CH;
constexpr uint32_t O_PAR = O_Y0, O_XR = O_XG + 32768;
constexpr uint32_t O_A = 8 * SLOT;
constexpr uint32_t O_RED1 = 13 * SLOT, O_RED2 = O_RED1 + 4096;
constexpr uint32_t O_BAR = 14 * SLOT, O_V3 = O_BAR + 1056, O_V4 = O_V3 + 256, O_ML = O_V4 + 448;
static_assert(8 * KST_W <= O_FT && O_FT >= 7 * SLOT && 7 * KST_W + 32 * KP_P <= 7 * SLOT, "smem map");
constexpr u64 W3SLOT = 0xDC98DC98DCBA98DCull, W4SLOT = 0x543210DC76543210ull;
constexpr uint32_t SMEM_BYTES = 232448;
static_assert(O_WS + 2048 <= 14 * SLOT && O_ML + 68 <= SMEM_BYTES, "smem map");

enum {
    B_XG = 0, B_HF = 2, B_ZF = 6, B_W3 = 14, B_LH0 = 30, B_PR = 32,
    B_W2 = 35, B_ZR = 39, B_W4 = 40,
    B_LH1 = 48,
    B_W1 = 50,
    B_KP = 64, B_TAB, B_CEND, B_CA, B_PH, B_PZ, B_CR0, B_CR1, B_E1 = 72, B_E2 = 76, B_ST = 80, B_T4 = 96,
    B_U = 104, B_FAR = 106, B_MOD0 = 108, B_MOD1, B_FTD, B_AUX, B_PX, B_V, B_V4, B_FB, B_ACC, B_DONE, B_SD, B_PB = 119,
    B_PAR = 128, B_XR
};

#define DI __device__ __forceinline__
#define SCHED_FENCE() asm volatile("{\n.reg .u32 t;\nmov.u32 t, %%clock;\nst.shared.u32 [%0], t;\n}" ::"r"(sm + O_ML + 64) : "memory")
DI void mwait(uint32_t bar) {
    asm volatile("{\n.reg .pred p;\nWL: mbarrier.try_wait.parity.shared::cta.b64 p, [%0], 0;\n@!p bra.uni WL;\n}" ::"r"(bar) : "memory");
}
DI void mwaitb(uint32_t bar) {
    asm volatile("{\n.reg .pred p;\n.reg .u32 n;\nmov.u32 n, 0;\n"
                 "WL: mbarrier.try_wait.parity.shared::cta.b64 p, [%0], 0;\n@p bra.uni WD;\n"
                 "add.u32 n, n, 1;\nsetp.lt.u32 p, n, 2000000;\n@p bra.uni WL;\ntrap;\nWD:\n}" ::"r"(bar) : "memory");
}
DI bool elect() { uint32_t r; asm volatile("{\n.reg .pred p;\nelect.sync _|p, 0xffffffff;\nselp.u32 %0, 1, 0, p;\n}" : "=r"(r)); return r; }
DI void marrive_n(uint32_t bar, int n) { asm volatile("mbarrier.arrive.shared::cta.b64 _, [%0], %1;" ::"r"(bar), "r"(n) : "memory"); }
DI void marrive(uint32_t bar) { asm volatile("mbarrier.arrive.shared::cta.b64 _, [%0];" ::"r"(bar) : "memory"); }
DI void marrive_rem(uint32_t bar) { asm volatile("mbarrier.arrive.shared::cluster.b64 _, [%0];" ::"r"(bar) : "memory"); }
DI uint32_t mapa(uint32_t a, uint32_t r) { uint32_t o; asm("mapa.shared::cluster.u32 %0, %1, %2;" : "=r"(o) : "r"(a), "r"(r)); return o; }
DI void nbar(int id, int n) { asm volatile("bar.sync %0, %1;" ::"r"(id), "r"(n) : "memory"); }
DI uint32_t lds32(uint32_t a) { uint32_t v; asm volatile("ld.shared.u32 %0, [%1];" : "=r"(v) : "r"(a)); return v; }
DI uint32_t lds32v(uint32_t a) { uint32_t v; asm volatile("ld.volatile.shared.u32 %0, [%1];" : "=r"(v) : "r"(a)); return v; }
DI float ldsf(uint32_t a) { float v; asm volatile("ld.shared.f32 %0, [%1];" : "=f"(v) : "r"(a)); return v; }
DI uint2 lds64(uint32_t a) { uint2 v; asm volatile("ld.shared.v2.u32 {%0,%1}, [%2];" : "=r"(v.x), "=r"(v.y) : "r"(a)); return v; }
DI float2 ldsf2(uint32_t a) { float2 v; asm volatile("ld.shared.v2.f32 {%0,%1}, [%2];" : "=f"(v.x), "=f"(v.y) : "r"(a)); return v; }
DI uint4 lds128(uint32_t a) { uint4 v; asm volatile("ld.shared.v4.u32 {%0,%1,%2,%3}, [%4];" : "=r"(v.x), "=r"(v.y), "=r"(v.z), "=r"(v.w) : "r"(a)); return v; }
DI float4 ldsf4(uint32_t a) { float4 v; asm volatile("ld.shared.v4.f32 {%0,%1,%2,%3}, [%4];" : "=f"(v.x), "=f"(v.y), "=f"(v.z), "=f"(v.w) : "r"(a)); return v; }
DI void sts32(uint32_t a, uint32_t v) { asm volatile("st.shared.u32 [%0], %1;" ::"r"(a), "r"(v) : "memory"); }
DI void stsf(uint32_t a, float v) { asm volatile("st.shared.f32 [%0], %1;" ::"r"(a), "f"(v) : "memory"); }
DI void sts64(uint32_t a, uint32_t x, uint32_t y) { asm volatile("st.shared.v2.u32 [%0], {%1,%2};" ::"r"(a), "r"(x), "r"(y) : "memory"); }
DI void stsf2(uint32_t a, float x, float y) { asm volatile("st.shared.v2.f32 [%0], {%1,%2};" ::"r"(a), "f"(x), "f"(y) : "memory"); }
DI void sts128(uint32_t a, uint32_t x, uint32_t y, uint32_t z, uint32_t w) { asm volatile("st.shared.v4.u32 [%0], {%1,%2,%3,%4};" ::"r"(a), "r"(x), "r"(y), "r"(z), "r"(w) : "memory"); }
DI void stsf4(uint32_t a, float x, float y, float z, float w) { asm volatile("st.shared.v4.f32 [%0], {%1,%2,%3,%4};" ::"r"(a), "f"(x), "f"(y), "f"(z), "f"(w) : "memory"); }
DI void ldsm4(uint32_t a, uint32_t& r0, uint32_t& r1, uint32_t& r2, uint32_t& r3) {
    asm volatile("ldmatrix.sync.aligned.m8n8.x4.shared.b16 {%0,%1,%2,%3}, [%4];" : "=r"(r0), "=r"(r1), "=r"(r2), "=r"(r3) : "r"(a));
}
DI void ldsm4t(uint32_t a, uint32_t& r0, uint32_t& r1, uint32_t& r2, uint32_t& r3) {
    asm volatile("ldmatrix.sync.aligned.m8n8.x4.trans.shared.b16 {%0,%1,%2,%3}, [%4];" : "=r"(r0), "=r"(r1), "=r"(r2), "=r"(r3) : "r"(a));
}
DI void stsm4(uint32_t a, uint32_t r0, uint32_t r1, uint32_t r2, uint32_t r3) {
    asm volatile("stmatrix.sync.aligned.m8n8.x4.shared.b16 [%0], {%1,%2,%3,%4};" ::"r"(a), "r"(r0), "r"(r1), "r"(r2), "r"(r3) : "memory");
}
DI void stsm4t(uint32_t a, uint32_t r0, uint32_t r1, uint32_t r2, uint32_t r3) {
    asm volatile("stmatrix.sync.aligned.m8n8.x4.trans.shared.b16 [%0], {%1,%2,%3,%4};" ::"r"(a), "r"(r0), "r"(r1), "r"(r2), "r"(r3) : "memory");
}
DI void mma(float (&d)[4], uint32_t a0, uint32_t a1, uint32_t a2, uint32_t a3, uint32_t b0, uint32_t b1) {
    asm volatile("mma.sync.aligned.m16n8k16.row.col.f32.bf16.bf16.f32 {%0,%1,%2,%3}, {%4,%5,%6,%7}, {%8,%9}, {%0,%1,%2,%3};"
                 : "+f"(d[0]), "+f"(d[1]), "+f"(d[2]), "+f"(d[3]) : "r"(a0), "r"(a1), "r"(a2), "r"(a3), "r"(b0), "r"(b1));
}
DI uint32_t pk(float lo, float hi) { uint32_t r; asm("cvt.rn.bf16x2.f32 %0, %1, %2;" : "=r"(r) : "f"(hi), "f"(lo)); return r; }
DI float blo(uint32_t v) { return __uint_as_float(v << 16); }
DI float bhi(uint32_t v) { return __uint_as_float(v & 0xffff0000u); }
DI float rbf(float v) { return __bfloat162float(__float2bfloat16_rn(v)); }
DI uint4 ldg128(const void* p) { uint4 v; asm volatile("ld.global.nc.L1::no_allocate.v4.u32 {%0,%1,%2,%3}, [%4];" : "=r"(v.x), "=r"(v.y), "=r"(v.z), "=r"(v.w) : "l"(p)); return v; }
DI uint32_t ldg32(const void* p) { uint32_t v; asm volatile("ld.global.nc.u32 %0, [%1];" : "=r"(v) : "l"(p)); return v; }
DI unsigned short ldg16(const bf16* p) { unsigned short v; asm volatile("ld.global.nc.u16 %0, [%1];" : "=h"(v) : "l"(p)); return v; }
DI float b2f(unsigned short h) { float v; asm volatile("{\n.reg .b32 t;\ncvt.u32.u16 t, %1;\nshl.b32 %0, t, 16;\n}" : "=f"(v) : "h"(h)); return v; }
DI uint4 ldw128(const void* p) { uint4 v; asm volatile("ld.global.v4.u32 {%0,%1,%2,%3}, [%4];" : "=r"(v.x), "=r"(v.y), "=r"(v.z), "=r"(v.w) : "l"(p) : "memory"); return v; }
DI uint32_t ldw32(const void* p) { uint32_t v; asm volatile("ld.global.u32 %0, [%1];" : "=r"(v) : "l"(p) : "memory"); return v; }
DI float ldgbf(const bf16* p) { unsigned short v; asm volatile("ld.global.nc.u16 %0, [%1];" : "=h"(v) : "l"(p)); return __uint_as_float((uint32_t)v << 16); }
DI uint4 ldc128(const void* p) { uint4 v; asm volatile("ld.global.L1::no_allocate.v4.u32 {%0,%1,%2,%3}, [%4];" : "=r"(v.x), "=r"(v.y), "=r"(v.z), "=r"(v.w) : "l"(p) : "memory"); return v; }
DI uint2 ldc64(const void* p) { uint2 v; asm volatile("ld.global.L1::no_allocate.v2.u32 {%0,%1}, [%2];" : "=r"(v.x), "=r"(v.y) : "l"(p) : "memory"); return v; }
DI uint32_t ldc32(const void* p) { uint32_t v; asm volatile("ld.global.L1::no_allocate.u32 %0, [%1];" : "=r"(v) : "l"(p) : "memory"); return v; }
DI void stg128(void* p, uint4 v) { asm volatile("st.global.v4.u32 [%0], {%1,%2,%3,%4};" ::"l"(p), "r"(v.x), "r"(v.y), "r"(v.z), "r"(v.w) : "memory"); }
DI void st_rlx(unsigned* p, unsigned v) { asm volatile("st.relaxed.gpu.global.u32 [%0], %1;" ::"l"(p), "r"(v) : "memory"); }
DI unsigned ld_rlx(const unsigned* p) { unsigned v; asm volatile("ld.relaxed.gpu.global.u32 %0, [%1];" : "=r"(v) : "l"(p) : "memory"); return v; }
DI void publish(unsigned* p, unsigned v) { asm volatile("st.release.gpu.global.u32 [%0], %1;" ::"l"(p), "r"(v) : "memory"); }
DI void poll(const unsigned* p, unsigned ep) {
    asm volatile("{\n.reg .pred p;\n.reg .u32 v;\n"
                 "PL: ld.acquire.gpu.global.u32 v, [%0];\nsetp.eq.u32 p, v, %1;\nvote.sync.all.pred p, p, 0xffffffff;\n@!p bra.uni PL;\n}" ::"l"(p), "r"(ep) : "memory");
}
DI unsigned pollb(const unsigned* p, unsigned ep, unsigned mask) {
    unsigned v;
    asm volatile("{\n.reg .pred p;\n.reg .u32 n, t;\nmov.u32 n, 0;\n"
                 "PL: ld.acquire.gpu.global.u32 %0, [%1];\nand.b32 t, %0, %3;\nsetp.eq.u32 p, t, %2;\nvote.sync.all.pred p, p, 0xffffffff;\n@p bra.uni PD;\n"
                 "add.u32 n, n, 1;\nsetp.lt.u32 p, n, 2000000;\n@p bra.uni PL;\ntrap;\nPD:\n}" : "=&r"(v) : "l"(p), "r"(ep), "r"(mask) : "memory");
    return v;
}
DI void tma2d(uint32_t dst, const CUtensorMap* m, int c0, int c1, uint32_t bar) {
    asm volatile("cp.async.bulk.tensor.2d.shared::cluster.global.mbarrier::complete_tx::bytes [%0], [%1, {%3,%4}], [%2];" ::"r"(dst), "l"(m), "r"(bar), "r"(c0), "r"(c1) : "memory");
}
DI void tma3d(uint32_t dst, const CUtensorMap* m, int c0, int c1, int c2, uint32_t bar) {
    asm volatile("cp.async.bulk.tensor.3d.shared::cluster.global.mbarrier::complete_tx::bytes [%0], [%1, {%3,%4,%5}], [%2];" ::"r"(dst), "l"(m), "r"(bar), "r"(c0), "r"(c1), "r"(c2) : "memory");
}
DI void tma3d_mc(uint32_t dst, const CUtensorMap* m, int c0, int c1, int c2, uint32_t bar) {
    asm volatile("cp.async.bulk.tensor.3d.shared::cluster.global.mbarrier::complete_tx::bytes.multicast::cluster [%0], [%1, {%3,%4,%5}], [%2], %6;" ::"r"(dst), "l"(m), "r"(bar), "r"(c0), "r"(c1), "r"(c2), "h"((unsigned short)3) : "memory");
}
DI void bulk_ld(uint32_t dst, const void* src, uint32_t bytes, uint32_t bar) {
    asm volatile("cp.async.bulk.shared::cluster.global.mbarrier::complete_tx::bytes [%0], [%1], %2, [%3];" ::"r"(dst), "l"(src), "r"(bytes), "r"(bar) : "memory");
}
DI void bulk_ld_mc(uint32_t dst, const void* src, uint32_t bytes, uint32_t bar) {
    asm volatile("cp.async.bulk.shared::cluster.global.mbarrier::complete_tx::bytes.multicast::cluster [%0], [%1], %2, [%3], %4;" ::"r"(dst), "l"(src), "r"(bytes), "r"(bar), "h"((unsigned short)3) : "memory");
}
DI void l2_prefetch(const void* p, uint32_t bytes) { asm volatile("cp.async.bulk.prefetch.L2.global [%0], %1;" ::"l"(p), "r"(bytes) : "memory"); }
DI void st_async(uint32_t dst, const uint32_t (&v)[4], uint32_t bar) {
    asm volatile("st.async.shared::cluster.mbarrier::complete_tx::bytes.v4.b32 [%0], {%1,%2,%3,%4}, [%5];" ::"r"(dst), "r"(v[0]), "r"(v[1]), "r"(v[2]), "r"(v[3]), "r"(bar) : "memory");
}
#define FENCE_ASYNC_S() asm volatile("fence.proxy.async.shared::cta;" ::: "memory")
#define FENCE_ASYNC_G() asm volatile("fence.proxy.async.global;" ::: "memory")
#define WG_FENCE() asm volatile("wgmma.fence.sync.aligned;" ::: "memory")
#define WG_COMMIT() asm volatile("wgmma.commit_group.sync.aligned;" ::: "memory")
#define WG_WAIT(n) asm volatile("wgmma.wait_group.sync.aligned %0;" ::"n"(n) : "memory")
template <int N> DI void pin(float (&d)[N]) {
#pragma unroll
    for (int i = 0; i < N; i++) asm volatile("" : "+f"(d[i])::"memory");
}
constexpr uint32_t SM_BASE = 1024;
DI uint64_t mkdesc(uint32_t off16, uint32_t off, uint32_t lbo) {
    uint32_t lo = off16 + (((SM_BASE + off) >> 4) | ((lbo >> 4) << 16));
    uint64_t d; asm("mov.b64 %0, {%1, %2};" : "=l"(d) : "r"(lo), "r"(0x40000040u)); return d;
}
DI uint32_t hadd2(uint32_t a, uint32_t b) { uint32_t d; asm("add.rn.bf16x2 %0, %1, %2;" : "=r"(d) : "r"(a), "r"(b)); return d; }
DI uint32_t hmul2(uint32_t a, uint32_t b) { uint32_t d; asm("mul.rn.bf16x2 %0, %1, %2;" : "=r"(d) : "r"(a), "r"(b)); return d; }
DI uint32_t hfma2(uint32_t a, uint32_t b, uint32_t c) { uint32_t d; asm("fma.rn.bf16x2 %0, %1, %2, %3;" : "=r"(d) : "r"(a), "r"(b), "r"(c)); return d; }
__device__ __forceinline__ void wgmma_ss_n64(float (&d)[32], uint64_t da, uint64_t db, int sc){
  asm volatile("{.reg .pred p; setp.ne.b32 p, %34, 0;\n wgmma.mma_async.sync.aligned.m64n64k16.f32.bf16.bf16 {%0,%1,%2,%3,%4,%5,%6,%7,%8,%9,%10,%11,%12,%13,%14,%15,%16,%17,%18,%19,%20,%21,%22,%23,%24,%25,%26,%27,%28,%29,%30,%31}, %32, %33, p, 1, 1, 0, 1;}\n"
   : "+f"(d[0]),"+f"(d[1]),"+f"(d[2]),"+f"(d[3]),"+f"(d[4]),"+f"(d[5]),"+f"(d[6]),"+f"(d[7]),"+f"(d[8]),"+f"(d[9]),"+f"(d[10]),"+f"(d[11]),"+f"(d[12]),"+f"(d[13]),"+f"(d[14]),"+f"(d[15]),"+f"(d[16]),"+f"(d[17]),"+f"(d[18]),"+f"(d[19]),"+f"(d[20]),"+f"(d[21]),"+f"(d[22]),"+f"(d[23]),"+f"(d[24]),"+f"(d[25]),"+f"(d[26]),"+f"(d[27]),"+f"(d[28]),"+f"(d[29]),"+f"(d[30]),"+f"(d[31])
   : "l"(da),"l"(db),"r"(sc));
}
__device__ __forceinline__ void wgmma_ss_n96(float (&d)[48], uint64_t da, uint64_t db, int sc){
  asm volatile("{.reg .pred p; setp.ne.b32 p, %50, 0;\n wgmma.mma_async.sync.aligned.m64n96k16.f32.bf16.bf16 {%0,%1,%2,%3,%4,%5,%6,%7,%8,%9,%10,%11,%12,%13,%14,%15,%16,%17,%18,%19,%20,%21,%22,%23,%24,%25,%26,%27,%28,%29,%30,%31,%32,%33,%34,%35,%36,%37,%38,%39,%40,%41,%42,%43,%44,%45,%46,%47}, %48, %49, p, 1, 1, 0, 1;}\n"
   : "+f"(d[0]),"+f"(d[1]),"+f"(d[2]),"+f"(d[3]),"+f"(d[4]),"+f"(d[5]),"+f"(d[6]),"+f"(d[7]),"+f"(d[8]),"+f"(d[9]),"+f"(d[10]),"+f"(d[11]),"+f"(d[12]),"+f"(d[13]),"+f"(d[14]),"+f"(d[15]),"+f"(d[16]),"+f"(d[17]),"+f"(d[18]),"+f"(d[19]),"+f"(d[20]),"+f"(d[21]),"+f"(d[22]),"+f"(d[23]),"+f"(d[24]),"+f"(d[25]),"+f"(d[26]),"+f"(d[27]),"+f"(d[28]),"+f"(d[29]),"+f"(d[30]),"+f"(d[31]),"+f"(d[32]),"+f"(d[33]),"+f"(d[34]),"+f"(d[35]),"+f"(d[36]),"+f"(d[37]),"+f"(d[38]),"+f"(d[39]),"+f"(d[40]),"+f"(d[41]),"+f"(d[42]),"+f"(d[43]),"+f"(d[44]),"+f"(d[45]),"+f"(d[46]),"+f"(d[47])
   : "l"(da),"l"(db),"r"(sc));
}
__device__ __forceinline__ void wgmma_ss_n128(float (&d)[64], uint64_t da, uint64_t db, int sc){
  asm volatile("{.reg .pred p; setp.ne.b32 p, %66, 0;\n wgmma.mma_async.sync.aligned.m64n128k16.f32.bf16.bf16 {%0,%1,%2,%3,%4,%5,%6,%7,%8,%9,%10,%11,%12,%13,%14,%15,%16,%17,%18,%19,%20,%21,%22,%23,%24,%25,%26,%27,%28,%29,%30,%31,%32,%33,%34,%35,%36,%37,%38,%39,%40,%41,%42,%43,%44,%45,%46,%47,%48,%49,%50,%51,%52,%53,%54,%55,%56,%57,%58,%59,%60,%61,%62,%63}, %64, %65, p, 1, 1, 0, 1;}\n"
   : "+f"(d[0]),"+f"(d[1]),"+f"(d[2]),"+f"(d[3]),"+f"(d[4]),"+f"(d[5]),"+f"(d[6]),"+f"(d[7]),"+f"(d[8]),"+f"(d[9]),"+f"(d[10]),"+f"(d[11]),"+f"(d[12]),"+f"(d[13]),"+f"(d[14]),"+f"(d[15]),"+f"(d[16]),"+f"(d[17]),"+f"(d[18]),"+f"(d[19]),"+f"(d[20]),"+f"(d[21]),"+f"(d[22]),"+f"(d[23]),"+f"(d[24]),"+f"(d[25]),"+f"(d[26]),"+f"(d[27]),"+f"(d[28]),"+f"(d[29]),"+f"(d[30]),"+f"(d[31]),"+f"(d[32]),"+f"(d[33]),"+f"(d[34]),"+f"(d[35]),"+f"(d[36]),"+f"(d[37]),"+f"(d[38]),"+f"(d[39]),"+f"(d[40]),"+f"(d[41]),"+f"(d[42]),"+f"(d[43]),"+f"(d[44]),"+f"(d[45]),"+f"(d[46]),"+f"(d[47]),"+f"(d[48]),"+f"(d[49]),"+f"(d[50]),"+f"(d[51]),"+f"(d[52]),"+f"(d[53]),"+f"(d[54]),"+f"(d[55]),"+f"(d[56]),"+f"(d[57]),"+f"(d[58]),"+f"(d[59]),"+f"(d[60]),"+f"(d[61]),"+f"(d[62]),"+f"(d[63])
   : "l"(da),"l"(db),"r"(sc));
}
__device__ __forceinline__ void wgmma_rs_n64(float (&d)[32], const uint32_t (&a)[4], uint64_t db, int sc){
  asm volatile("{.reg .pred p; setp.ne.b32 p, %37, 0;\n wgmma.mma_async.sync.aligned.m64n64k16.f32.bf16.bf16 {%0,%1,%2,%3,%4,%5,%6,%7,%8,%9,%10,%11,%12,%13,%14,%15,%16,%17,%18,%19,%20,%21,%22,%23,%24,%25,%26,%27,%28,%29,%30,%31}, {%32,%33,%34,%35}, %36, p, 1, 1, 1;}\n"
   : "+f"(d[0]),"+f"(d[1]),"+f"(d[2]),"+f"(d[3]),"+f"(d[4]),"+f"(d[5]),"+f"(d[6]),"+f"(d[7]),"+f"(d[8]),"+f"(d[9]),"+f"(d[10]),"+f"(d[11]),"+f"(d[12]),"+f"(d[13]),"+f"(d[14]),"+f"(d[15]),"+f"(d[16]),"+f"(d[17]),"+f"(d[18]),"+f"(d[19]),"+f"(d[20]),"+f"(d[21]),"+f"(d[22]),"+f"(d[23]),"+f"(d[24]),"+f"(d[25]),"+f"(d[26]),"+f"(d[27]),"+f"(d[28]),"+f"(d[29]),"+f"(d[30]),"+f"(d[31])
   : "r"(a[0]),"r"(a[1]),"r"(a[2]),"r"(a[3]),"l"(db),"r"(sc));
}
__device__ __forceinline__ void wgmma_rs_n128(float (&d)[64], const uint32_t (&a)[4], uint64_t db, int sc){
  asm volatile("{.reg .pred p; setp.ne.b32 p, %69, 0;\n wgmma.mma_async.sync.aligned.m64n128k16.f32.bf16.bf16 {%0,%1,%2,%3,%4,%5,%6,%7,%8,%9,%10,%11,%12,%13,%14,%15,%16,%17,%18,%19,%20,%21,%22,%23,%24,%25,%26,%27,%28,%29,%30,%31,%32,%33,%34,%35,%36,%37,%38,%39,%40,%41,%42,%43,%44,%45,%46,%47,%48,%49,%50,%51,%52,%53,%54,%55,%56,%57,%58,%59,%60,%61,%62,%63}, {%64,%65,%66,%67}, %68, p, 1, 1, 1;}\n"
   : "+f"(d[0]),"+f"(d[1]),"+f"(d[2]),"+f"(d[3]),"+f"(d[4]),"+f"(d[5]),"+f"(d[6]),"+f"(d[7]),"+f"(d[8]),"+f"(d[9]),"+f"(d[10]),"+f"(d[11]),"+f"(d[12]),"+f"(d[13]),"+f"(d[14]),"+f"(d[15]),"+f"(d[16]),"+f"(d[17]),"+f"(d[18]),"+f"(d[19]),"+f"(d[20]),"+f"(d[21]),"+f"(d[22]),"+f"(d[23]),"+f"(d[24]),"+f"(d[25]),"+f"(d[26]),"+f"(d[27]),"+f"(d[28]),"+f"(d[29]),"+f"(d[30]),"+f"(d[31]),"+f"(d[32]),"+f"(d[33]),"+f"(d[34]),"+f"(d[35]),"+f"(d[36]),"+f"(d[37]),"+f"(d[38]),"+f"(d[39]),"+f"(d[40]),"+f"(d[41]),"+f"(d[42]),"+f"(d[43]),"+f"(d[44]),"+f"(d[45]),"+f"(d[46]),"+f"(d[47]),"+f"(d[48]),"+f"(d[49]),"+f"(d[50]),"+f"(d[51]),"+f"(d[52]),"+f"(d[53]),"+f"(d[54]),"+f"(d[55]),"+f"(d[56]),"+f"(d[57]),"+f"(d[58]),"+f"(d[59]),"+f"(d[60]),"+f"(d[61]),"+f"(d[62]),"+f"(d[63])
   : "r"(a[0]),"r"(a[1]),"r"(a[2]),"r"(a[3]),"l"(db),"r"(sc));
}

struct C2 { float r, i; };
DI C2 cmul(C2 a, C2 b) { C2 o; o.r = fmaf(a.r, b.r, -a.i * b.i); o.i = fmaf(a.r, b.i, a.i * b.r); return o; }
DI C2 cpow(float a2, float th, float l) {
    float m; asm("ex2.approx.ftz.f32 %0, %1;" : "=f"(m) : "f"(a2 * l));
    float ph = th * l; ph -= rintf(ph); ph *= 6.283185307179586f;
    C2 o; o.r = m * __cosf(ph); o.i = m * __sinf(ph); return o;
}
constexpr float GK0 = 0.7978845608028654f, GK1 = 0.044715f;
DI uint32_t gelu_tail(uint32_t y, uint32_t A, uint32_t B) {
    uint32_t u = hmul2(y, hfma2(hmul2(y, y), A, B)), t;
    asm("tanh.approx.bf16x2 %0, %1;" : "=r"(t) : "r"(u));
    return hfma2(y, t, y);
}
DI void row_stats(float s, float q, float& mu, float& r) { mu = s * (1.f / 512); r = rsqrtf(fmaxf(q * (1.f / 512) - mu * mu, 0.f) + 1e-5f); }
struct RowC { uint32_t nmu, A, B; };
DI RowC rowc(float mu, float r) { RowC c; float B = GK0 * r, A = GK1 * B * r * r; c.nmu = pk(-mu, -mu); c.A = pk(A, A); c.B = pk(B, B); return c; }
template <int N> DI void gelu16(const float (&acc)[N], int i, uint32_t vaddr, const RowC& lo, const RowC& hi, uint32_t (&o)[4]) {
    uint2 v = lds64(vaddr);
    o[0] = gelu_tail(hfma2(v.x, lo.nmu, pk(acc[8 * i + 0], acc[8 * i + 1])), lo.A, lo.B);
    o[1] = gelu_tail(hfma2(v.x, hi.nmu, pk(acc[8 * i + 2], acc[8 * i + 3])), hi.A, hi.B);
    o[2] = gelu_tail(hfma2(v.y, lo.nmu, pk(acc[8 * i + 4], acc[8 * i + 5])), lo.A, lo.B);
    o[3] = gelu_tail(hfma2(v.y, hi.nmu, pk(acc[8 * i + 6], acc[8 * i + 7])), hi.A, hi.B);
}
DI float qsum(float v) { v += __shfl_xor_sync(~0u, v, 1); v += __shfl_xor_sync(~0u, v, 2); return v; }
DI void fma8(float (&a)[8], uint4 w, float s) {
    a[0] = fmaf(blo(w.x), s, a[0]); a[1] = fmaf(bhi(w.x), s, a[1]); a[2] = fmaf(blo(w.y), s, a[2]); a[3] = fmaf(bhi(w.y), s, a[3]);
    a[4] = fmaf(blo(w.z), s, a[4]); a[5] = fmaf(bhi(w.z), s, a[5]); a[6] = fmaf(blo(w.w), s, a[6]); a[7] = fmaf(bhi(w.w), s, a[7]);
}
DI void red64(float (&a)[8], int lane, uint32_t dst) {
    bool u = lane & 16, v = lane & 8;
    float b[4], c[2];
#pragma unroll
    for (int i = 0; i < 4; i++) b[i] = (u ? a[4 + i] : a[i]) + __shfl_xor_sync(~0u, u ? a[i] : a[4 + i], 16);
#pragma unroll
    for (int i = 0; i < 2; i++) c[i] = (v ? b[2 + i] : b[i]) + __shfl_xor_sync(~0u, v ? b[i] : b[2 + i], 8);
    stsf2(dst + (lane & 7) * 32 + (lane >> 3) * 8, c[0], c[1]);
}
DI void ln_rows(const uint4 (&v)[4], int lane, unsigned* dst, unsigned ep) {
    float s[2], q[2];
#pragma unroll
    for (int r = 0; r < 2; r++) {
        s[r] = 0.f; q[r] = 0.f;
#pragma unroll
        for (int j = 0; j < 2; j++) {
            uint32_t w[4] = {v[2 * r + j].x, v[2 * r + j].y, v[2 * r + j].z, v[2 * r + j].w};
#pragma unroll
            for (int k = 0; k < 4; k++) { float a = blo(w[k]), c = bhi(w[k]); s[r] += a + c; q[r] = fmaf(a, a, fmaf(c, c, q[r])); }
        }
    }
    bool u = lane & 16;
    float ss = (u ? s[1] : s[0]) + __shfl_xor_sync(~0u, u ? s[0] : s[1], 16);
    float qq = (u ? q[1] : q[0]) + __shfl_xor_sync(~0u, u ? q[0] : q[1], 16);
#pragma unroll
    for (int o = 8; o; o >>= 1) { ss += __shfl_xor_sync(~0u, ss, o); qq += __shfl_xor_sync(~0u, qq, o); }
    float mu, r; row_stats(ss, qq, mu, r); r = rbf(r);
    if ((lane & 15) == 0) st_rlx(dst, pk(-mu * r, r) | (ep << 31));
}
template <int W> DI void conv_near(float (&acc)[8][4], uint32_t ua, uint32_t n1, uint32_t n2) {
#pragma unroll 1
    for (int r = 0; r < 8; r++) {
        uint32_t u[12][2];
#pragma unroll
        for (int i = 5; i >= (W ? 0 : 2); i--) ldsm4(ua + i * 256, u[2 * i][0], u[2 * i][1], u[2 * i + 1][0], u[2 * i + 1][1]);
#pragma unroll
        for (int q = 0; q < 5; q++) {
            if (q < 4 || r < 2) {
                const uint2 a = lds64(n1 + q * 64), e = lds64(n2 + q * 64);
#pragma unroll
                for (int j = 7; j >= (W ? 0 : q); j--) mma(acc[j], a.x, a.y, e.x, e.y, u[j - q + 4][0], u[j - q + 4][1]);
            }
        }
        ua -= 16; n1 += 8; n2 += 8;
    }
}
template <int W> DI void conv_far(float (&acc)[8][4], uint32_t bx, int ph, uint32_t ft) {
#pragma unroll
    for (int gi = 0; gi < 4; gi++) {
        const uint32_t aa = bx + ((gi & 1) ? B5_O : B3_O) + ((gi >> 1) ? (ph ^ 1) * (H2O - 16) : ph * H2O);
        uint32_t a[6][4]; uint2 f[6];
#pragma unroll
        for (int k = 0; k < (W ? 6 : 2); k++) ldsm4t(aa + k * 256, a[k][0], a[k][1], a[k][2], a[k][3]);
#pragma unroll
        for (int i = 0; i < (W ? 6 : 4); i++) f[i] = lds64(ft + gi * 448 + i * 64);
#pragma unroll
        for (int t = 0; t < 3; t++)
#pragma unroll
            for (int j = 7; j >= 0; j--) {
                const int k = (j >> 1) + 4 * W - 2 - t, i = 2 * t + (j & 1);
                if (k >= 0) mma(acc[j], a[k][0], a[k][1], a[k][2], a[k][3], f[i].x, f[i].y);
            }
    }
    if (W) {
#pragma unroll
        for (int gi = 0; gi < 3; gi++) {
            const uint32_t aa = bx + B9_O + gi * 2176 + (gi == 0 ? (ph ^ 1) * (H3O - 16) : ph * H3O);
            uint32_t a[4][4]; uint2 f[8];
#pragma unroll
            for (int k = 0; k < 4; k++) ldsm4t(aa + k * 256, a[k][0], a[k][1], a[k][2], a[k][3]);
#pragma unroll
            for (int i = 0; i < (gi < 2 ? 8 : 2); i++) f[i] = lds64(ft + 1792 + gi * 576 + i * 64);
#pragma unroll
            for (int t = 0; t < (gi < 2 ? 4 : 1); t++)
#pragma unroll
                for (int j = 7; j >= 2 * t; j--) {
                    const int k = (j >> 1) - t, i = 2 * t + (j & 1);
                    mma(acc[j], a[k][0], a[k][1], a[k][2], a[k][3], f[i].x, f[i].y);
                }
        }
    }
}

__global__ void __launch_bounds__(384, 1) __cluster_dims__(2, 1, 1)
fused_kernel(const __grid_constant__ Params P, const __grid_constant__ Maps M) {
    extern __shared__ __align__(1024) unsigned char smem_raw[];
    const uint32_t sm = (uint32_t)__cvta_generic_to_shared(smem_raw);
    const uint32_t bars = sm + O_BAR;
#define BAR(i) (bars + 8u * (uint32_t)(i))
#define WARRIVE_N(i, n) do { __syncwarp(); if (lane == 0) marrive_n(BAR(i), n); } while (0)
#define WARRIVE(i) do { __syncwarp(); if (lane == 0) marrive(BAR(i)); } while (0)
    const int b = blockIdx.x, tid = (int)threadIdx.x - 128, lane = tid & 31;
    const int warp = __shfl_sync(~0u, tid >> 5, 0), wg = warp >> 2, wq = warp & 3, t128 = tid & 127;
    const int g = lane >> 2, c = lane & 3;
    const int p = b & 1, kq = (b >> 1) & 3, hh = kq >> 1, gg = 2 * p + (kq & 1), tau = 2 * (b >> 3) + hh, fj = b & 7;

    if (wg >= 0) {
        const int ch = wq;
        unsigned ep;
        float dskip;
        {
            if (warp == 0 && elect()) {
                asm volatile("mbarrier.init.shared::cta.b64 [%0], 1;\nmbarrier.init.shared::cta.b64 [%0+8], 1;\n"
                             "mbarrier.arrive.expect_tx.shared::cta.b64 _, [%0], 6176;\nmbarrier.arrive.expect_tx.shared::cta.b64 _, [%0+8], 16384;\n"
                             "fence.mbarrier_init.release.cluster;" ::"r"(BAR(B_PAR)) : "memory");
#pragma unroll
                for (int i = 0; i < 6; i++) bulk_ld(sm + O_PAR + i * 1024, P.par[i] + b * 512, 1024, BAR(B_PAR));
#pragma unroll
                for (int i = 0; i < 2; i++) bulk_ld(sm + O_PAR + 6144 + i * 16, P.par[6 + i] + (b >> 1) * 8, 16, BAR(B_PAR));
            }
            if (warp == 0) TS(53);
            asm volatile("barrier.cluster.arrive.relaxed.aligned;" ::: "memory");
            sts128(sm + O_U + warp * U_H + (lane & 7) * 16, 0, 0, 0, 0);
#pragma unroll
            for (int i = 0; i < 5; i++) sts128(sm + O_NT + (i < 4 ? i * 4096 : 4 * NT_CH - 4096) + tid * 16, 0, 0, 0, 0);
#pragma unroll
            for (int i = 0; i < 4; i++) sts128(sm + O_FT + (i < 3 ? i * 4096 : 4 * FT_CH - 4096) + tid * 16, 0, 0, 0, 0);
            asm volatile("barrier.cluster.wait.aligned;" ::: "memory");
            if (warp == 1 && elect()) bulk_ld(sm + O_XR, P.x + b * 8192, 16384, BAR(B_XR));
            if (warp == 0) TS(64);
            mwait(BAR(B_PAR));
            if (warp == 0 && elect()) {
                tma3d_mc(sm + O_XG + p * 8192, &tmX, 8 * (b >> 1), 0, 4 * p, BAR(B_XG));
                tma3d_mc(sm + O_XG + 16384 + p * 8192, &tmX, 8 * (b >> 1), 128, 4 * p, BAR(B_XG + 1));
            }
            if (warp == 0) TS(61);
            const uint32_t pa = sm + O_PAR + ch * 256 + wg * 128 + lane * 4, pb = sm + O_PAR + 6144 + p * 8 + (ch >> 1) * 4;
            const uint32_t r_ldt = lds32(pb), r_are = lds32(pa), r_aim = lds32(pa + 1024), r_bre = lds32(pa + 2048), r_bim = lds32(pa + 3072),
                           r_cre = lds32(pa + 4096), r_cim = lds32(pa + 5120), r_dk = lds32(pb + 16);
            ep = ld_rlx(P.s->epoch + (b * 32 + lane));
            dskip = (ch & 1) ? bhi(r_dk) : blo(r_dk);
            const float dt = rbf(expf((ch & 1) ? bhi(r_ldt) : blo(r_ldt)));
            const uint32_t kst = sm + warp * KST_W, ka = kst + lane * 8;
            C2 w8[2], z1[2], h2[2], f[2], f2[2], f4[2], f6[2], a[2];
#pragma unroll
            for (int m = 0; m < 2; m++) {
                C2 B = {m ? bhi(r_bre) : blo(r_bre), m ? bhi(r_bim) : blo(r_bim)}, C = {m ? bhi(r_cre) : blo(r_cre), m ? bhi(r_cim) : blo(r_cim)};
                C2 cb = cmul(C, B); f[m].r = cb.r * dt; f[m].i = -cb.i * dt; a[m] = f[m];
            }
#define KSTORE(row, v) sts64(ka + (row) * KST_P, pk(v[0].r, v[0].i), pk(v[1].r, v[1].i))
#define KMUL(o, x, y) do { o[0] = cmul(x[0], y[0]); o[1] = cmul(x[1], y[1]); } while (0)
            KSTORE(32, f);
#pragma unroll
            for (int m = 0; m < 2; m++) {
                float a2 = dt * (m ? bhi(r_are) : blo(r_are)) * 1.4426950408889634f;
                float th = dt * (m ? bhi(r_aim) : blo(r_aim)) * 0.15915494309189535f;
                w8[m] = cpow(a2, th, 8.f); z1[m] = cpow(a2, -th, 1.f); h2[m] = cpow(a2, -th, 256.f);
            }
            KMUL(f, f, z1); KSTORE(33, f); KMUL(f2, f, z1); KSTORE(34, f2); KMUL(f, f2, z1); KSTORE(35, f);
            KMUL(f4, f, z1); KSTORE(36, f4); KMUL(f, f4, z1); KSTORE(37, f); KMUL(f6, f, z1); KSTORE(38, f6);
            KMUL(f, f6, z1); KSTORE(39, f);
            KMUL(f2, f2, h2); KSTORE(41, f2); KMUL(f6, f6, h2); KSTORE(43, f6);
            KMUL(a, a, h2); KSTORE(40, a); KMUL(f4, f4, h2); KSTORE(42, f4);
            KMUL(a, a, h2); KSTORE(44, a); KMUL(f4, f4, h2); KSTORE(45, f4);
            KMUL(a, a, h2); KSTORE(46, a); KMUL(f4, f4, h2); KSTORE(47, f4);
#pragma unroll 1
            for (int r = 48; r < 53; r++) { KMUL(a, a, h2); KSTORE(r, a); }
            a[0] = C2{1.f, 0.f}; a[1] = a[0];
#pragma unroll 4
            for (int r = 0; r < 32; r++) { KSTORE(r, a); KMUL(a, a, w8); }
            if (warp == 0) TS(62);
            ep++;
            mwait(BAR(B_XR));
            uint4 xa[4];
#pragma unroll
            for (int i = 0; i < 4; i++) xa[i] = lds128(sm + O_XR + warp * 2048 + i * 512 + lane * 16);
            ln_rows(xa, lane, P.s->stats + ((wq >> 1) * 1024 + 8 * b + 4 * wg + 2 * (wq & 1) + (lane >> 4)), ep);
            if (warp == 0) TS(52);
            __syncwarp();
            float d[6][4];
#pragma unroll
            for (int i = 0; i < 6; i++) { d[i][0] = d[i][1] = d[i][2] = d[i][3] = 0.f; }
            const uint32_t aA = kst + (lane & 15) * KST_P + (lane >> 4) * 16;
            const uint32_t aB = kst + (32 + 8 * (lane >> 4) + (lane & 7)) * KST_P + ((lane >> 3) & 1) * 16;
            const uint32_t aC = kst + (48 + (lane & 7)) * KST_P + (lane >> 3) * 16;
#pragma unroll
            for (int k2 = 0; k2 < 4; k2++) {
                uint32_t t0, t1, t2, t3; ldsm4(aC + k2 * 64, t0, t1, t2, t3);
#pragma unroll
                for (int e = 0; e < 2; e++) {
                    uint32_t x0, x1, x2, x3, y0, y1, y2, y3, b0, b1, b2, b3;
                    ldsm4(aA + k2 * 64 + e * 32, x0, x1, x2, x3); ldsm4(aA + 16 * KST_P + k2 * 64 + e * 32, y0, y1, y2, y3);
                    ldsm4(aB + k2 * 64 + e * 32, b0, b1, b2, b3);
                    mma(d[0], x0, x1, x2, x3, b0, b1); mma(d[1], x0, x1, x2, x3, b2, b3); mma(d[2], x0, x1, x2, x3, e ? t2 : t0, e ? t3 : t1);
                    mma(d[3], y0, y1, y2, y3, b0, b1); mma(d[4], y0, y1, y2, y3, b2, b3); mma(d[5], y0, y1, y2, y3, e ? t2 : t0, e ? t3 : t1);
                }
            }
            __syncwarp();
#pragma unroll
            for (int i = 0; i < 6; i++) {
                uint32_t o = kst + ((i / 3) * 16 + g) * KP_P + (i % 3) * 32 + c * 8;
                stsf2(o, d[i][0], d[i][1]); stsf2(o + 8 * KP_P, d[i][2], d[i][3]);
            }
            WARRIVE(B_KP);
            if (warp == 0) TS(1);
        }
        uint2 xr[8];
        {
            uint32_t st[8], bad;
            bool first = true;
            do {
#pragma unroll
                for (int j = 0; j < 2; j++)
                    asm volatile("ld.relaxed.gpu.global.v4.u32 {%0,%1,%2,%3}, [%4];" : "=r"(st[4 * j]), "=r"(st[4 * j + 1]), "=r"(st[4 * j + 2]), "=r"(st[4 * j + 3])
                                 : "l"(P.s->stats + (1024 * j + 4 * tid)) : "memory");
                if (first) {
                    first = false;
                    mwait(BAR(B_KP));
                    const uint32_t k0 = sm + ch * KST_W, k1 = k0 + 4 * KST_W, nt = sm + O_NT + ch * NT_CH + (2 + 32 * wg + lane) * 4;
                    float v[8], pv;
                    if (wg == 0) {
                        float4 p0 = ldsf4(k0 + lane * KP_P), p1 = ldsf4(k0 + lane * KP_P + 16), q0 = ldsf4(k1 + lane * KP_P), q1 = ldsf4(k1 + lane * KP_P + 16);
                        v[0] = p0.x + q0.x; v[1] = p0.y + q0.y; v[2] = p0.z + q0.z; v[3] = p0.w + q0.w;
                        v[4] = p1.x + q1.x; v[5] = p1.y + q1.y; v[6] = p1.z + q1.z; v[7] = p1.w + q1.w;
                        pv = __shfl_up_sync(~0u, v[7], 1);
                        if (lane == 0) { pv = 0.f; v[0] += dskip; }
                    } else {
                        float4 p0 = ldsf4(k0 + lane * KP_P + 32), q0 = ldsf4(k1 + lane * KP_P + 32);
                        uint32_t eo = lane == 0 ? 31 * KP_P + 28 : 48;
                        float ex = ldsf(k0 + eo) + ldsf(k1 + eo);
                        v[0] = v[1] = p0.x + q0.x; v[2] = p0.y + q0.y; v[3] = v[4] = v[5] = p0.z + q0.z; v[6] = p0.w + q0.w;
                        v[7] = __shfl_down_sync(~0u, v[0], 1); if (lane == 31) v[7] = ex;
                        pv = lane == 0 ? ex : v[0];
                        if (lane >= 24)
                            sts32(sm + O_NT + ch * NT_CH + 66 * 4 + c * NT_R + (g & 1) * NT_B, pk(c == 3 ? 0.f : ex, ex));
                    }
#pragma unroll
                    for (int i = 0; i < 8; i++) { const uint32_t t = pk(v[i], i ? v[i - 1] : pv); sts32(nt + i * NT_R, t); sts32(nt + i * NT_R + NT_B, t); }
                    WARRIVE(B_TAB);
                    if (wq == 0) TS(2 + wg);
                    mwait(BAR(B_XG + wg));
#pragma unroll
                    for (int j = 0; j < 8; j++) xr[j] = lds64(sm + O_XG + wg * 16384 + j * 2048 + t128 * 16 + p * 8);
                    if (wq == 0) TS(4 + wg);
                }
                bad = 0;
#pragma unroll
                for (int j = 0; j < 8; j++) { st[j] ^= ep << 31; bad |= st[j]; }
            } while (__any_sync(~0u, (int)bad < 0));
            if (wq == 0) TS(6 + wg);
            mwait(BAR(B_MOD0));
            if (wq == 0) TS(8 + wg);
            const uint4 mc = lds128(sm + O_ML);
            uint32_t h0[8], h1[8];
#pragma unroll
            for (int j = 0; j < 8; j++) {
                const uint32_t r2 = __byte_perm(st[j], 0, 0x3232), nm2 = __byte_perm(st[j], 0, 0x1010);
                h0[j] = hfma2(hfma2(xr[j].x, r2, nm2), mc.z, mc.x); h1[j] = hfma2(hfma2(xr[j].y, r2, nm2), mc.w, mc.y);
            }
            const uint32_t uo = sm + O_U + (t128 & 1) * U_H + (8 + 64 * wg + (t128 >> 1)) * 16;
#define TR4(h, sel) __byte_perm(h[0], h[1], sel), __byte_perm(h[2], h[3], sel), __byte_perm(h[4], h[5], sel), __byte_perm(h[6], h[7], sel)
            sts128(uo, TR4(h0, 0x5410)); sts128(uo + U_CH, TR4(h0, 0x7632)); sts128(uo + 2 * U_CH, TR4(h1, 0x5410)); sts128(uo + 3 * U_CH, TR4(h1, 0x7632));
            WARRIVE(B_U + wg);
        }
        {
            float acc[8][4];
#pragma unroll
            for (int j = 0; j < 8; j++) { acc[j][0] = acc[j][1] = acc[j][2] = acc[j][3] = 0.f; }
            const int ph = (lane >> 3) & 1, mr = 8 * (lane >> 4) + (lane & 7), o = g - 2 * c;
            const uint32_t ua = sm + O_U + ch * U_CH + ph * U_H + (64 * wg - 24 + mr) * 16;
            const uint32_t na = sm + O_NT + ch * NT_CH + (o & 7) * NT_R, n1 = na + (o < 0 ? NT_B + 4 : 8), n2 = na + (o < 0 ? 0 : NT_B + 4);
            const uint32_t bx = sm + O_BOX + ch * BOX_CH + (mr + 1) * 16, ft = sm + O_FT + ch * FT_CH + (8 + o) * 8;
            mwait(BAR(B_TAB)); mwait(BAR(B_U));
            if (wg) {
                mwait(BAR(B_U + 1));
                if (wq == 0) TS(57);
                {
                    const uint32_t ub = sm + O_U + ch * U_CH + 112 + (lane >> 1) * 16, bo = sm + O_BOX + ch * BOX_CH;
                    const int hf = lane & 1;
                    if (lane < 3) sts128(bo + (lane == 2 ? B9_O + H3O : lane * 3200 + H2O), 0, 0, 0, 0);
#pragma unroll 2
                    for (int it = 0; it < 6; it++) {
                        const uint2 u0 = lds64(ub + it * 256 + hf * U_H + 8);
                        const uint4 u1 = lds128(ub + it * 256 + (hf ? 16 : U_H)), u2 = lds128(ub + it * 256 + hf * U_H + 16);
                        const uint32_t E[9] = {u0.x, u0.y, u1.x, u1.y, u1.z, u1.w, u2.x, u2.y, u2.z};
                        uint32_t O[8], A[8], F[6];
#pragma unroll
                        for (int k = 0; k < 8; k++) { O[k] = __byte_perm(E[k], E[k + 1], 0x5432); A[k] = hadd2(E[k], O[k]); }
#pragma unroll
                        for (int k = 0; k < 6; k++) F[k] = hadd2(A[k], A[k + 1]);
                        const uint32_t o2 = bo + hf * H2O + (16 * it + (lane >> 1) + 1) * 16, o3 = o2 - hf * (H2O - H3O);
                        sts128(o2 + B5_O, hadd2(F[1], E[3]), hadd2(F[2], E[4]), hadd2(F[3], E[5]), hadd2(F[4], E[6]));
                        sts128(o2 + B3_O, hadd2(O[3], A[4]), hadd2(O[4], A[5]), hadd2(O[5], A[6]), hadd2(O[6], A[7]));
                        if (it < 4) {
                            sts128(o3 + B9_O, hadd2(F[0], hadd2(F[2], E[4])), hadd2(F[1], hadd2(F[3], E[5])), hadd2(F[2], hadd2(F[4], E[6])), hadd2(F[3], hadd2(F[5], E[7])));
                            sts128(o3 + B7_O, hadd2(hadd2(O[0], A[1]), F[2]), hadd2(hadd2(O[1], A[2]), F[3]), hadd2(hadd2(O[2], A[3]), F[4]), hadd2(hadd2(O[3], A[4]), F[5]));
                            sts128(o3 + B2_O, A[4], A[5], A[6], A[7]);
                        }
                    }
                    WARRIVE(B_FAR);
                }
                if (wq == 0) TS(11);
                conv_near<1>(acc, ua, n1, n2);
                if (wq == 0) TS(13);
                mwait(BAR(B_FTD));
                if (wq == 0) TS(15);
                conv_far<1>(acc, bx, ph, ft);
            } else {
                if (wq == 0) TS(10);
                conv_near<0>(acc, ua, n1, n2);
                if (wq == 0) TS(12);
                mwait(BAR(B_FTD)); mwait(BAR(B_FAR));
                if (wq == 0) TS(14);
                conv_far<0>(acc, bx, ph, ft);
            }
            if (wq == 0) TS(16 + wg);
            const uint32_t yb = wg ? sm + O_BOX + B9_O : sm + O_Y0, ych = wg ? BOX_CH : Y_CH;
            __syncwarp();
#pragma unroll
            for (int j = 0; j < 8; j += 2)
                stsm4t(yb + ch * ych + ph * H3O + (8 * j + mr) * 16, pk(acc[j][0], acc[j][1]), pk(acc[j][2], acc[j][3]),
                       pk(acc[j + 1][0], acc[j + 1][1]), pk(acc[j + 1][2], acc[j + 1][3]));
            mwait(BAR(B_MOD1));
            const uint2 ga = lds64(sm + O_ML + 16);
            nbar(1 + wg, 128);
            uint32_t yq[4][4];
#pragma unroll
            for (int k = 0; k < 4; k++) { uint4 t = lds128(yb + k * ych + (t128 & 1) * H3O + (t128 >> 1) * 16); yq[k][0] = t.x; yq[k][1] = t.y; yq[k][2] = t.z; yq[k][3] = t.w; }
            __syncwarp();
#pragma unroll
            for (int j = 0; j < 4; j++)
                sts128(yb + (lane >> 3) * ych + ((lane >> 2) & 1) * H3O + wq * 256 + ((lane & 3) * 4 + (j ^ ((lane >> 1) & 3))) * 16,
                       hfma2(ga.x, __byte_perm(yq[0][j], yq[1][j], 0x5410), xr[2 * j].x), hfma2(ga.y, __byte_perm(yq[2][j], yq[3][j], 0x5410), xr[2 * j].y),
                       hfma2(ga.x, __byte_perm(yq[0][j], yq[1][j], 0x7632), xr[2 * j + 1].x), hfma2(ga.y, __byte_perm(yq[2][j], yq[3][j], 0x7632), xr[2 * j + 1].y));
            __syncwarp();
            uint4* xo = (uint4*)P.s->x1 + (b * 1024 + 512 * wg + 128 * wq + lane);
            uint4 t[4];
#pragma unroll
            for (int k = 0; k < 4; k++) t[k] = lds128(yb + k * ych + (lane >> 4) * H3O + wq * 256 + ((lane & 15) ^ ((lane >> 3) & 3)) * 16);
#pragma unroll
            for (int k = 0; k < 4; k++) stg128(xo + 32 * k, t[k]);
            if (wq == 0) TS(66 + wg);
            WARRIVE(B_CEND);
            if (wg) { if (lane == 0) marrive(BAR(B_PX)); }
            else {
                nbar(1, 128);
                if (wq == 0 && elect()) publish(P.s->f0 + ((b >> 4) * 32 + (b & 15)), ep);
            }
            if (warp == 0) TS(18);
        }
        {
            uint32_t xv[32]; uint4 sbv[8], ccv[8];
#pragma unroll 1
            for (int it = 0; it < 4; it++) {
                const int a = it >> 1;
                if (!(it & 1)) {
                    poll(P.s->f0 + (a * 256 + warp * 32 + (lane & 15)), ep);
                    if (warp == 0) TS(20 + a);
                    const uint2* xp = P.s->x1 + ((16 * warp) * 2048 + 1024 * a + 32 * tau + lane);
#pragma unroll
                    for (int q = 0; q < 16; q++) { uint2 t = ldc64(xp + q * 2048); xv[2 * q] = t.x; xv[2 * q + 1] = t.y; }
                    if (a == 0) {
#pragma unroll
                        for (int q = 0; q < 8; q++) { sbv[q] = ldw128(P.s->modf + (64 * warp + 8 * q)); ccv[q] = ldw128(P.s->modf + (512 + 64 * warp + 8 * q)); }
                        mwait(BAR(B_CEND));
                    }
                }
                float s1 = 0.f, s2 = 0.f, s3 = 0.f, s4 = 0.f;
#pragma unroll
                for (int q = 0; q < 8; q++) {
                    uint32_t u = hadd2(hadd2(xv[4 * q], xv[4 * q + 1]), hadd2(xv[4 * q + 2], xv[4 * q + 3]));
                    uint32_t v = hfma2(xv[4 * q + 3], xv[4 * q + 3], hfma2(xv[4 * q + 2], xv[4 * q + 2], hfma2(xv[4 * q + 1], xv[4 * q + 1], hmul2(xv[4 * q], xv[4 * q]))));
                    s1 += blo(u); s3 += bhi(u); s2 += blo(v); s4 += bhi(v);
                }
                if (warp == 0) TS(68 + it);
                const uint32_t ra = sm + O_RED1 + (it & 1) * 4096 + (32 * a + lane) * 8;
                stsf2(ra + warp * 512, s1 + s3, s2 + s4);
                if (!(it & 1)) {
                    nbar(3, 256);
                    s1 = s2 = s3 = s4 = 0.f;
#pragma unroll
                    for (int w = 0; w < 4; w++) { float2 t = ldsf2(ra + w * 1024), u = ldsf2(ra + w * 1024 + 512); s1 += t.x; s2 += t.y; s3 += u.x; s4 += u.y; }
                    float mu, r; row_stats(s1 + s3, s2 + s4, mu, r);
                    const uint32_t r2 = pk(r, r), nm2 = pk(-mu * blo(r2), -mu * blo(r2));
                    const uint32_t ar = sm + O_A + warp * 8192 + (32 * a + lane) * 128;
#pragma unroll
                    for (int q = 0; q < 8; q++) {
                        xv[4 * q] = hfma2(hfma2(xv[4 * q], r2, nm2), ccv[q].x, sbv[q].x); xv[4 * q + 1] = hfma2(hfma2(xv[4 * q + 1], r2, nm2), ccv[q].y, sbv[q].y);
                        xv[4 * q + 2] = hfma2(hfma2(xv[4 * q + 2], r2, nm2), ccv[q].z, sbv[q].z); xv[4 * q + 3] = hfma2(hfma2(xv[4 * q + 3], r2, nm2), ccv[q].w, sbv[q].w);
                        sts128(ar + ((q ^ (lane & 7)) << 4), xv[4 * q], xv[4 * q + 1], xv[4 * q + 2], xv[4 * q + 3]);
                    }
                }
            }
        }
        uint32_t swz[4];
#pragma unroll
        for (int q = 0; q < 4; q++) swz[q] = sm + wq * 2048 + (lane & 15) * 128 + (((2 * q + (lane >> 4)) ^ (lane & 7)) << 4);
        uint32_t hres[16];
        {
            float acc[32];
            mwait(BAR(B_W1 + wg));
            FENCE_ASYNC_S();
            nbar(3, 256);
            if (warp == 0) TS(22);
            const uint32_t ra = sm + O_RED2 + c * 1024 + (16 * wq + g) * 8;
            const float2 t0 = ldsf2(ra), t1 = ldsf2(ra + 512), t2 = ldsf2(ra + 64), t3 = ldsf2(ra + 576);
#pragma unroll
            for (int q = 0; q < 4; q++) ldsm4(swz[q] + O_A + (2 * gg + wg) * 8192, hres[4 * q], hres[4 * q + 1], hres[4 * q + 2], hres[4 * q + 3]);
            sts32(sm + O_ML + 64, hres[15] ^ __float_as_uint(t3.x));
#pragma unroll 1
            for (int s = 0; s < 4; s++) {
                WG_FENCE();
#pragma unroll
                for (int k = 0; k < 8; k++)
                    wgmma_ss_n64(acc, mkdesc(s * 1024, O_A + (k >> 2) * 8192 + (k & 3) * 32, 16), mkdesc(wg * 4096 + s * 1024, k * 2048, 16), s | k);
                WG_COMMIT();
                WG_WAIT(1);
                if (s > 0 && lane == 0) marrive(BAR(B_E1 + s - 1));
            }
            float m0, r0, m1, r1;
            row_stats(qsum(t0.x + t1.x), qsum(t0.y + t1.y), m0, r0); row_stats(qsum(t2.x + t3.x), qsum(t2.y + t3.y), m1, r1);
            r0 *= GK0; r1 *= GK0;
            const uint32_t n0 = pk(-m0 * r0, -m0 * r0), n1 = pk(-m1 * r1, -m1 * r1), kA = pk(GK1 / (GK0 * GK0), GK1 / (GK0 * GK0)), kB = 0x3f803f80u;
            WG_WAIT(0); pin(acc);
            if (wq == 0) TS(23 + wg);
            if (lane == 0) marrive(BAR(B_E1 + 3));
            mwait(BAR(B_V));
            uint2 vv[4];
#pragma unroll
            for (int q = 0; q < 4; q++) vv[q] = lds64(sm + O_V3 + wg * 128 + q * 32 + c * 8);
            uint32_t o[16];
#pragma unroll
            for (int q = 0; q < 4; q++) {
                o[4 * q] = gelu_tail(hfma2(vv[q].x, n0, pk(acc[8 * q] * r0, acc[8 * q + 1] * r0)), kA, kB);
                o[4 * q + 1] = gelu_tail(hfma2(vv[q].x, n1, pk(acc[8 * q + 2] * r1, acc[8 * q + 3] * r1)), kA, kB);
                o[4 * q + 2] = gelu_tail(hfma2(vv[q].y, n0, pk(acc[8 * q + 4] * r0, acc[8 * q + 5] * r0)), kA, kB);
                o[4 * q + 3] = gelu_tail(hfma2(vv[q].y, n1, pk(acc[8 * q + 6] * r1, acc[8 * q + 7] * r1)), kA, kB);
                if (q == 0) mwait(BAR(B_E1 + 3));
                stsm4(swz[q] + O_A + wg * 8192, o[4 * q], o[4 * q + 1], o[4 * q + 2], o[4 * q + 3]);
            }
            __syncwarp();
            const uint32_t stg = sm + O_A + wg * 8192 + wq * 2048;
            bf16* ho = P.s->h + (((wq >> 1) * 1024 + 32 * tau + (wq & 1) * 16 + (lane >> 3) + 2) * 512 + 128 * gg + 64 * wg + (lane & 7) * 8);
            uint4 t[4];
#pragma unroll
            for (int k = 0; k < 4; k++) { int row = 4 * k + (lane >> 3); t[k] = lds128(stg + row * 128 + (((lane & 7) ^ (row & 7)) << 4)); }
#pragma unroll
            for (int k = 0; k < 4; k++) stg128(ho + k * 2048, t[k]);
            WARRIVE(B_PH);
            if (wq == 0) TS(25 + wg);
        }
        asm volatile("setmaxnreg.inc.sync.aligned.u32 232;");
        {
            float acc[32];
#pragma unroll 1
            for (int s = 0; s < 4; s++) {
                mwait(BAR(B_W2 + s)); mwait(BAR(B_HF + s));
                if (wq == 0 && s == 0) TS(27 + wg);
                WG_FENCE();
#pragma unroll
                for (int k = 0; k < 8; k++)
                    wgmma_ss_n64(acc, mkdesc(s * 1024, O_A + (k >> 2) * 8192 + (k & 3) * 32, 16), mkdesc(wg * 4096 + s * 1024, k * 2048, 16), s | k);
                WG_COMMIT();
                WG_WAIT(1);
                if (s > 0 && lane == 0) marrive(BAR(B_E2 + s - 1));
            }
            WG_WAIT(0); pin(acc);
            if (wq == 0) TS(31 + wg);
            if (lane == 0) marrive(BAR(B_E2 + 3));
            float s0 = 0.f, q0 = 0.f, s1 = 0.f, q1 = 0.f;
            mwait(BAR(B_E2));
#pragma unroll
            for (int q = 0; q < 4; q++) {
                uint32_t o[4];
#pragma unroll
                for (int e = 0; e < 4; e++) {
                    float z0 = fmaf(acc[8 * q + 2 * e], 0.5f / GK0, blo(hres[4 * q + e])), z1 = fmaf(acc[8 * q + 2 * e + 1], 0.5f / GK0, bhi(hres[4 * q + e]));
                    if (e & 1) { s1 += z0 + z1; q1 = fmaf(z0, z0, fmaf(z1, z1, q1)); } else { s0 += z0 + z1; q0 = fmaf(z0, z0, fmaf(z1, z1, q0)); }
                    o[e] = pk(z0, z1);
                }
                stsm4(swz[q] + wg * 8192, o[0], o[1], o[2], o[3]);
            }
            __syncwarp();
            uint4* zo = P.s->z + ((tau * 8 + 2 * gg) * 512 + warp * 128 + lane);
            uint4 t[4];
#pragma unroll
            for (int k = 0; k < 4; k++) t[k] = lds128(sm + warp * 2048 + k * 512 + lane * 16);
#pragma unroll
            for (int k = 0; k < 4; k++) stg128(zo + 32 * k, t[k]);
            s0 = qsum(s0); q0 = qsum(q0); s1 = qsum(s1); q1 = qsum(q1);
            if (c < 2) P.s->zst[(tau * 8 + 2 * gg) * 64 + 16 * warp + g + 8 * c] = c ? make_float2(s1, q1) : make_float2(s0, q0);
            WARRIVE(B_PZ);
            if (wq == 0) TS(33 + wg);
        }
        uint32_t Ho[14][4], Hp[14][4];
        float acc[64], rs0, rs1;
        const uint32_t peer = p ^ 1;
#define W3A(i) ((uint32_t)((W3SLOT >> (4 * (i))) & 15) * SLOT)
#define W4A(i) ((uint32_t)((W4SLOT >> (4 * (i))) & 15) * SLOT)
#define G4PAIR(j, H, k0, first) do { \
            if (j) mwait(BAR(B_W4 + (j) / 2)); \
            WG_FENCE(); \
            _Pragma("unroll") \
            for (int k = 0; k < (((j) & 4) ? 6 : 8); k++) \
                wgmma_rs_n128(acc, H[(k0) + k], mkdesc(0, W4A((j) + (k >> 2)) + (k & 3) * 2048, (((j) & 4) && k >= 4) ? 4096 : 8192), !(first) || k); \
            WG_COMMIT(); } while (0)
#define PACK8(k) pk(acc[8 * (k)] * rs0, acc[8 * (k) + 1] * rs0), pk(acc[8 * (k) + 2] * rs1, acc[8 * (k) + 3] * rs1), \
                 pk(acc[8 * (k) + 4] * rs0, acc[8 * (k) + 5] * rs0), pk(acc[8 * (k) + 6] * rs1, acc[8 * (k) + 7] * rs1)
        {
            float acc2[48];
            const float2* zs = P.s->zst + (((tau & ~1) + wg) * 512 + c * 128 + 16 * wq + g);
            uint2 t0, t1, t2, t3;
#pragma unroll 1
            for (int s = 0; s < 8; s++) {
                mwait(BAR(B_W3 + s)); mwait(BAR(B_ZF + (s & 6) + wg));
                if (wq == 0 && s == 0) TS(35 + wg);
                const uint32_t wa = (s < 2 ? 12 + s : 6 + s) * 1024;
                WG_FENCE();
#pragma unroll
                for (int k = 0; k < 4; k++)
                    wgmma_ss_n128(acc, mkdesc(((s & 6) + wg) * 1024 + (s & 1) * 512, k * 32, 16), mkdesc(wa, k * 2048, 8192), s | k);
                WG_COMMIT();
                if (s == 4) { t0 = ldc64(zs); t1 = ldc64(zs + 64); t2 = ldc64(zs + 8); t3 = ldc64(zs + 72); }
                WG_WAIT(1);
                if (s > 0 && lane == 0) { marrive(BAR(B_ST + s - 1)); if (s == 6) marrive_rem(mapa(BAR(B_CR0), peer)); }
            }
            float m0, m1;
            row_stats(qsum(__uint_as_float(t0.x) + __uint_as_float(t1.x)), qsum(__uint_as_float(t0.y) + __uint_as_float(t1.y)), m0, rs0);
            row_stats(qsum(__uint_as_float(t2.x) + __uint_as_float(t3.x)), qsum(__uint_as_float(t2.y) + __uint_as_float(t3.y)), m1, rs1);
            const RowC lo = rowc(m0, rs0), hi = rowc(m1, rs1);
            rs0 *= 0.5f; rs1 *= 0.5f;
            const uint32_t va = sm + O_V4 + c * 8;
            const uint32_t l0 = mapa(sm + wg * SLOT + t128 * 16, peer), lb0 = mapa(BAR(wg), peer);
#pragma unroll
            for (int s = 0; s < 8; s++) {
                if (s == 0) mwait(BAR(B_W3 + 8));
                WG_FENCE();
#pragma unroll
                for (int k = 0; k < 4; k++)
                    wgmma_ss_n96(acc2, mkdesc(wg * 1024, (s & 6) * SLOT + (s & 1) * 8192 + k * 32, 16), mkdesc(0, W3A(8 + s) + k * 2048, 8192 + 64), s | k);
                WG_COMMIT();
                WG_WAIT(1);
                if (lane == 0) { marrive(BAR(B_ST + 7 + s)); if (s == 6) marrive_rem(mapa(BAR(B_CR1), peer)); }
                if (s == 0) { pin(acc); if (wq == 0) TS(37 + wg); mwait(BAR(B_CR0)); }
                gelu16(acc, s, va + s * 32, lo, hi, Ho[s]);
                mwait(BAR(s < 7 ? B_W3 + 9 + s : B_W4));
                st_async(l0 + 10 * SLOT + s * 2048, Ho[s], lb0 + 8 * B_LH0);
                if (warp == 0 && (s == 3 || s == 4)) TS(s == 3 ? 65 : 75);
            }
            G4PAIR(0, Ho, 0, 1);
            WG_WAIT(1); pin(acc2);
            if (wq == 0) TS(39 + wg);
            if (lane == 0) marrive(BAR(B_ST + 15));
            mwait(BAR(B_CR1));
#pragma unroll
            for (int k = 0; k < 3; k++) { gelu16(acc2, k, va + 256 + k * 32, lo, hi, Ho[8 + k]); st_async(l0 + 8 * SLOT + k * 2048, Ho[8 + k], lb0 + 8 * B_LH1); }
            mwait(BAR(B_LH0 + wg));
#pragma unroll
            for (int k = 0; k < 8; k++) { uint4 t = lds128(sm + (10 + wg) * SLOT + k * 2048 + t128 * 16); Hp[k][0] = t.x; Hp[k][1] = t.y; Hp[k][2] = t.z; Hp[k][3] = t.w; }
            G4PAIR(2, Hp, 0, 0);
            WG_WAIT(1);
            if (lane == 0) marrive(BAR(B_T4));
#pragma unroll
            for (int k = 3; k < 6; k++) { gelu16(acc2, k, va + 256 + k * 32, lo, hi, Ho[8 + k]); st_async(l0 + 8 * SLOT + k * 2048, Ho[8 + k], lb0 + 8 * B_LH1); }
        }
        if (wq == 0) TS(41 + wg);
        G4PAIR(4, Ho, 8, 0);
        WG_WAIT(1);
        if (lane == 0) marrive(BAR(B_T4 + 1));
        mwait(BAR(B_LH1 + wg));
#pragma unroll
        for (int k = 0; k < 6; k++) { uint4 t = lds128(sm + (8 + wg) * SLOT + k * 2048 + t128 * 16); Hp[8 + k][0] = t.x; Hp[8 + k][1] = t.y; Hp[8 + k][2] = t.z; Hp[8 + k][3] = t.w; }
        G4PAIR(6, Hp, 8, 0);
        WG_WAIT(1);
        if (lane == 0) marrive(BAR(B_T4 + 2));
        WG_WAIT(0); pin(acc);
        if (wq == 0) TS(43 + wg);
        if (lane == 0) marrive(BAR(B_CA));
        const bool own = wg == hh;
#pragma unroll
        for (int k = 0; k < 8; k++) sts128(sm + (10 + wg) * SLOT + k * 2048 + t128 * 16, PACK8(k));
        FENCE_ASYNC_S();
        WARRIVE(B_PB + (own ? 0 : 2));
        if (own) mwait(BAR(B_FB));
        if (!own && wq == 0) TS(72);
        G4PAIR(8, Ho, 0, 1); G4PAIR(10, Hp, 0, 0);
        if (!own && wq == 0) TS(73);
        G4PAIR(12, Ho, 8, 0);
        if (!own && wq == 0) TS(74);
        G4PAIR(14, Hp, 8, 0);
        if (!own && lane == 0) marrive(BAR(B_FB));
        if (own) mwait(BAR(B_SD));
        WG_WAIT(0); pin(acc);
        if (wq == 0) TS(45 + own);
        {
            uint4* po = (own ? (uint4*)(smem_raw + 11 * SLOT) : P.s->part + ((b ^ 4) * 3 + 1) * 1024) + t128;
#pragma unroll
            for (int k = 0; k < 8; k++) po[k * 128] = make_uint4(PACK8(k));
            WARRIVE(own ? B_ACC : B_PB + 1);
        }
        if (!own) {
            const int tok0 = (wq >> 1) * 1024 + 32 * tau + (wq & 1) * 16;
            uint32_t gb[16], x1[32], z[32], s[32];
#pragma unroll
            for (int n = 0; n < 16; n++) gb[n] = ldw32(P.s->modf + (1024 + 128 * gg + 8 * n + 2 * c));
            mwait(BAR(B_ZR));
#pragma unroll
            for (int n = 0; n < 16; n++) {
                const uint32_t xa = sm + 7 * SLOT + (2 * n + (c >> 1)) * 512 + (16 * wq + g) * 8 + (c & 1) * 4;
                x1[2 * n] = lds32(xa); x1[2 * n + 1] = lds32(xa + 64);
            }
#pragma unroll
            for (int q = 0; q < 8; q++) ldsm4(swz[q & 3] + 6 * SLOT + (q >> 2) * 8192, z[4 * q], z[4 * q + 1], z[4 * q + 2], z[4 * q + 3]);
#pragma unroll
            for (int k = 0; k < 32; k++) s[k] = 0;
#pragma unroll 1
            for (int e = 0; e < 2; e++) {
                mwait(BAR(B_PR + 2 * e)); mwait(BAR(e ? B_ACC : B_PR + 1));
                if (wq == 0) TS(47 + e);
                const uint32_t pa = sm + (8 + 2 * e) * SLOT + t128 * 16;
#pragma unroll
                for (int k = 0; k < 8; k++) {
                    const uint4 t = lds128(pa + k * 2048), u = lds128(pa + SLOT + k * 2048);
                    s[4 * k] = hadd2(s[4 * k], hadd2(t.x, u.x)); s[4 * k + 1] = hadd2(s[4 * k + 1], hadd2(t.y, u.y));
                    s[4 * k + 2] = hadd2(s[4 * k + 2], hadd2(t.z, u.z)); s[4 * k + 3] = hadd2(s[4 * k + 3], hadd2(t.w, u.w));
                }
            }
#pragma unroll
            for (int q = 0; q < 8; q++)
                stsm4(swz[q & 3] + 6 * SLOT + (q >> 2) * 8192, hfma2(gb[2 * q], hadd2(z[4 * q], s[4 * q]), x1[4 * q]), hfma2(gb[2 * q], hadd2(z[4 * q + 1], s[4 * q + 1]), x1[4 * q + 1]),
                      hfma2(gb[2 * q + 1], hadd2(z[4 * q + 2], s[4 * q + 2]), x1[4 * q + 2]), hfma2(gb[2 * q + 1], hadd2(z[4 * q + 3], s[4 * q + 3]), x1[4 * q + 3]));
            __syncwarp();
            const uint32_t stg = sm + 6 * SLOT + wq * 2048;
            bf16* oo = P.out + ((tok0 + (lane >> 4)) * 512 + 128 * gg + (lane & 15) * 8);
            uint4 t[8];
#pragma unroll
            for (int k = 0; k < 8; k++) { int row = 2 * k + (lane >> 4); t[k] = lds128(stg + ((lane >> 3) & 1) * 8192 + row * 128 + (((lane & 7) ^ (row & 7)) << 4)); }
#pragma unroll
            for (int k = 0; k < 8; k++) stg128(oo + k * 1024, t[k]);
            if (wq == 0) TS(51);
            if (lane == 0) marrive(BAR(B_DONE));
        }
    } else {
        unsigned ep;
        {
            if (elect()) {
                const int cnt = wq < 2 ? 1 : 8;
#pragma unroll
                for (int i = 0; i < 32; i++) asm volatile("mbarrier.init.shared::cta.b64 [%0], %1;" ::"r"(BAR(32 * wq) + 8 * i), "r"((i >= 8 && wq == 3) ? 4 : cnt) : "memory");
                asm volatile("fence.mbarrier_init.release.cluster;" ::: "memory");
                if (wq == 3) asm volatile("prefetch.tensormap [%0];" ::"l"(&tmX) : "memory");
            }
            __syncwarp();
            if (wq < 2) {
                const int i = t128, tx = i < B_W2 ? 16384 : i < B_LH1 ? ((i >= B_W4 && (i & 2)) ? 24576 : 32768) : i < B_W1 ? 12288 : 65536;
                asm volatile("mbarrier.arrive.expect_tx.shared::cta.b64 _, [%0], %1;" ::"r"(BAR(i)), "r"(tx) : "memory");
            }
            SCHED_FENCE();
            const int rg = b >> 4, cg = b & 15;
            uint4 wv[4];
            unsigned short cr[4];
#pragma unroll
            for (int i = 0; i < 4; i++) cr[i] = ldg16(P.c + (64 * rg + (t128 >> 3) + 16 * i));
            ep = ld_rlx(P.s->epoch + (b * 32 + lane));
            const bf16* wm = P.wmod + ((64 * rg + (t128 >> 3)) * 3072 + 64 * cg + (t128 & 7) * 8);
#pragma unroll
            for (int i = 0; i < 4; i++) wv[i] = ldg128(wm + i * 16 * 3072);
            asm volatile("barrier.cluster.arrive.relaxed.aligned;" ::: "memory");
            SCHED_FENCE();
            if (wq == 0) TS(77);
            if ((sm & 0xffffffu) != SM_BASE) __trap();
            asm volatile("barrier.cluster.wait.aligned;" ::: "memory");
            asm volatile("add.u32 %0, %0, 1;" : "+r"(ep));
            const unsigned tag = ep & 0xffu;
            float sc[4];
#pragma unroll
            for (int i = 0; i < 4; i++) { const float v = b2f(cr[i]); sc[i] = rbf(__fdividef(v, 1.f + __expf(-v))); }
            unsigned* dst = P.s->modp + (rg * 3072 + 64 * cg + t128);
#pragma unroll 1
            for (int j = 0;; j++) {
                if ((j == 1 && wq < 2) || j == 3) {
                    const int sg = j - 1 + wq, cn = 4 * b + (lane >> 3);
                    float v = __uint_as_float(pollb(P.s->modp + ((lane & 7) * 3072 + sg * 512 + cn), tag, 0xffu) & 0xffffff00u);
                    v += __shfl_xor_sync(~0u, v, 1); v += __shfl_xor_sync(~0u, v, 2); v += __shfl_xor_sync(~0u, v, 4);
                    const bf16 o = __float2bfloat16_rn(rbf(v) + ((sg == 1 || sg == 4) ? 1.f : 0.f));
                    if (sg < 3) *(bf16*)(smem_raw + O_ML + sg * 8 + (lane >> 3) * 2) = o; else P.s->modf[(sg - 3) * 512 + cn] = o;
                    WARRIVE_N(j == 1 ? B_MOD0 : B_MOD1, j == 1 ? 2 : 1);
                    if (wq == 0) TS(54 + (j >> 1));
                }
                if (j == 3) {
                    mwaitb(BAR(wq == 2 ? B_PX : B_CEND));
                    if (wq >= 2 && elect()) {
                        if (wq == 2) publish(P.s->f0 + (256 + (b >> 4) * 32 + (b & 15)), ep);
                        else tma2d(sm + 7 * SLOT, &tmW1, 128 * gg + 64, 384, BAR(B_W1 + 1));
                    }
                    if (wq == 2) TS(19);
                }
                float a[8] = {0.f, 0.f, 0.f, 0.f, 0.f, 0.f, 0.f, 0.f};
#pragma unroll
                for (int i = 0; i < 4; i++) fma8(a, wv[i], sc[i]);
                const uint32_t ws = sm + O_WS + (j & 1) * 1024;
                red64(a, lane, ws + wq * 256);
                unsigned* dcur = dst;
                int pitch = 3072;
                const int id = (j - 2) * 128 + b, cc = id >> 3;
                if (j < 2) { wm += 1024; dst += 1024; }
                else {
                    pitch = cc < 8 ? 512 : 1792;
                    wm = (cc < 8 ? P.w1 : P.w3 - 512) + (64 * cc + (64 * (id & 7) + (t128 >> 3)) * pitch + (t128 & 7) * 8);
                    dst = P.s->csum + ((id & 7) * 2304 + 64 * cc + t128);
                    sc[0] = sc[1] = sc[2] = sc[3] = 1.f;
                }
                nbar(4, 128);
                if (wq < 2) {
                    float s = (ldsf(ws + t128 * 4) + ldsf(ws + 256 + t128 * 4)) + (ldsf(ws + 512 + t128 * 4) + ldsf(ws + 768 + t128 * 4));
                    st_rlx(dcur, ((__float_as_uint(s) + 0x80u) & 0xffffff00u) | tag);
                }
                if (wq == 0) TS(78 + j);
                if (id >= 288) break;
#pragma unroll
                for (int i = 0; i < 4; i++) wv[i] = ldg128(wm + i * 16 * pitch);
                if (j == 0 && (lane & 7) < 4) asm volatile("prefetch.global.L2 [%0];" ::"l"(wm + (1024 + (lane & 7) * 16 * 3072)));
                if (j == 1 && elect()) {
                    asm volatile("prefetch.tensormap [%0];" ::"l"(&tmW1 + wq) : "memory"); asm volatile("prefetch.tensormap [%0];" ::"l"(&tmW4 + wq) : "memory");
                    l2_prefetch(P.w1 + (b * 2048 + wq * 512), 1024); l2_prefetch(P.w3 + (b * 7168 + wq * 1792), 3584);
                }
                if (j != 1) continue;
                mwaitb(BAR(B_KP));
#pragma unroll 1
                for (int h = 0; h < 2; h++) {
                    float v[4];
#pragma unroll
                    for (int it = 0; it < 4; it++) {
                        const int l = 16 * lane + (h ? 1040 + (it & 1) * 512 - (it >> 1) * 8 : 516 + 4 * it);
                        const int col = l < 1024 ? 12 + 2 * ((l >> 8) & 1) + ((l >> 2) & 1) : 12 + (l >> 8);
                        const uint32_t o = sm + wq * KST_W + ((l & 255) >> 3) * KP_P + col * 4;
                        v[it] = ldsf(o) + ldsf(o + 4 * KST_W);
                    }
                    const uint32_t ft = sm + O_FT + wq * FT_CH + 64 + lane * 8;
#pragma unroll
                    for (int it = 0; it < 4; it++) {
                        float pv = __shfl_sync(~0u, ((it & 1) && lane == 31) ? v[it & 2] : v[it], lane - 1);
                        if (lane == 0 && !(h && (it & 1))) pv = 0.f;
                        const uint32_t d = ft + (h ? 1792 + (it >> 1) * 576 + (it & 1) * 256 : it * 448), t = pk(v[it], pv);
                        sts32(d, t);
                        if (!(h && (it & 1) && lane >= 24)) sts32(d + 68, t);
                        if (lane == 31 && !h) {
                            const uint32_t u = t << 16;
                            sts32(d + 8, u); sts32(d + 76, u);
                            if (it == 3) { const uint32_t e = ft + 2944 - 248; sts32(e, t & 0xffffu); sts32(e + 68, t & 0xffffu); sts32(e + 8, u); sts32(e + 76, u); }
                        }
                    }
                }
                WARRIVE(B_FTD);
                mwaitb(BAR(B_TAB)); mwaitb(BAR(B_FTD));
                if (elect()) {
                    tma2d(sm + wq * SLOT, &tmW1, 128 * gg, 128 * wq, BAR(B_W1));
                    if (wq < 3) tma2d(sm + (4 + wq) * SLOT, &tmW1, 128 * gg + 64, 128 * wq, BAR(B_W1 + 1));
                    l2_prefetch(P.w2 + (b * 2048 + wq * 512), 1024);
                    l2_prefetch(P.w4 + (b * 7168 + wq * 1792), 3584);
                }
                if (wq == 0) TS(58);
            }
            WARRIVE(B_AUX);
            if (wq == 0) TS(60);
        }
        asm volatile("setmaxnreg.dec.sync.aligned.u32 40;");
#pragma unroll 1
        for (int i0 = wq * 32; i0 < 176; i0 += 128) {
            const int i = min(i0 + lane, 175);
            const unsigned* s = P.s->csum + (i < 64 ? 128 * gg + 2 * i : 384 + 224 * fj + 2 * i);
            unsigned t[8][2], bad; int n = 0;
            do {
                bad = 0;
#pragma unroll
                for (int r = 0; r < 8; r++) asm volatile("ld.relaxed.gpu.global.v2.u32 {%0,%1}, [%2];" : "=r"(t[r][0]), "=r"(t[r][1]) : "l"(s + r * 2304) : "memory");
#pragma unroll
                for (int r = 0; r < 8; r++) bad |= (t[r][0] ^ ep) | (t[r][1] ^ ep);
                if (++n > 2000000) __trap();
            } while (__any_sync(~0u, bad & 0xffu));
            float a0 = 0.f, a1 = 0.f;
#pragma unroll
            for (int r = 0; r < 8; r++) { a0 += __uint_as_float(t[r][0] & 0xffffff00u); a1 += __uint_as_float(t[r][1] & 0xffffff00u); }
            sts32(sm + O_V3 + (i >> 3) * 32 + (i & 3) * 8 + (i & 4), pk(a0, a1));
            if (i0 < 64) WARRIVE_N(B_V, 2);
        }
        WARRIVE(B_V4);
        if (wq == 0) TS(76);
        if (wq == 0) {
            mwaitb(BAR(B_AUX)); mwaitb(BAR(B_V4));
#pragma unroll 1
            for (int i = 0; i < 32; i++) {
                const int j = i & 15;
                int wb, c0, c1, c2, d; const CUtensorMap* m;
                if (i < 16) {
                    wb = i == 0 ? B_CEND : i == 1 ? B_E1 + 3 : i < 10 ? B_E2 + i - 2 : B_ST + i - 4;
                    m = &tmW3 + (i >> 3); c0 = 224 * fj + (i >> 3) * 128; c1 = 64 * (i & 7); c2 = 0;
                    d = (W3SLOT >> (4 * j)) & 15;
                } else {
                    wb = j < 8 ? B_ST + 8 + (j | 1) : j < 10 ? B_ST + 15 : B_T4 + (j >> 1) - 5;
                    m = &tmW4 + ((j & 5) == 5); c0 = 0; c1 = 224 * (fj ^ ((j >> 1) & 1)) + 64 * ((j & 1) + ((j >> 1) & 2)); c2 = 2 * (gg ^ 1 ^ (j >> 3));
                    d = (W4SLOT >> (4 * j)) & 15;
                }
                mwaitb(BAR(wb));
                if (elect()) tma3d(sm + d * SLOT, m, c0, c1, c2, BAR(i < 16 ? B_W3 + i : B_W4 + (j >> 1)));
            }
            P.s->epoch[b * 32 + lane] = ep;
        } else if (wq == 1) {
            pollb(P.s->fh + (((tau + ((lane & 4) ? ((lane & 1) ? 1 : 31) : 0)) & 31) * 32 + (lane & 3)), ep, ~0u);
            TS(84);
            if (elect()) {
                FENCE_ASYNC_G();
#pragma unroll
                for (int q = 0; q < 4; q++)
                    tma3d_mc(sm + O_A + q * SLOT + p * 8192, &tmH, 128 * q + 64 * p, 32 * tau + (q == 0 ? 1 : q == 1 ? 3 : q == 2 ? 0 : 4), 0, BAR(B_HF + q));
            }
            pollb(P.s->fz + (((tau & ~1) + ((lane >> 2) & 1)) * 32 + (lane & 3)), ep, ~0u);
            TS(86);
            if (elect()) {
                FENCE_ASYNC_G();
#pragma unroll
                for (int q = 0; q < 4; q++)
                    bulk_ld_mc(sm + (2 * q + p) * SLOT, P.s->z + (((tau & ~1) + p) * 8 + 2 * q) * 512, 16384, BAR(B_ZF + 2 * q + p));
            }
            mwaitb(BAR(B_CA));
            if (elect()) {
                bulk_ld(sm + 6 * SLOT, P.s->z + (tau * 8 + 2 * gg) * 512, 16384, BAR(B_ZR));
                tma3d(sm + 7 * SLOT, &tmX1, 128 * tau, 0, 32 * gg, BAR(B_ZR));
            }
            mwaitb(BAR(B_SD));
#pragma unroll 1
            for (int s = 0; s < 3; s++) {
                const int sl = s == 0 ? 2 : s - 1;
                pollb(P.s->fp + (b * 32 + sl), ep, ~0u);
                if (elect()) { FENCE_ASYNC_G(); bulk_ld(sm + (8 + s) * SLOT, P.s->part + (b * 3 + sl) * 1024, 16384, BAR(B_PR + s)); }
            }
        } else {
            if (wq == 2) {
#pragma unroll 1
                for (int i = 0; i < 4; i++) {
                    mwaitb(BAR(B_E1 + i));
                    if (elect()) {
                        tma2d(sm + i * SLOT, &tmW2, 128 * gg, 128 * i, BAR(B_W2 + i));
                        tma2d(sm + (4 + i) * SLOT, &tmW2, 128 * gg + 64, 128 * i, BAR(B_W2 + i));
                    }
                }
            }
#pragma unroll 1
            for (int e = 0; e < 3; e++) {
                const int x = wq == 2 ? 4 - e : 1;
                mwaitb(BAR(e == 0 ? B_PH + 3 - wq : (e == 2 && wq == 3) ? B_DONE : B_PB + x - 1));
                if (e == 2 && wq == 3) break;
                if (elect()) {
                    if (e == 1) {
                        asm volatile("cp.async.bulk.global.shared::cta.bulk_group [%0], [%1], 16384;\ncp.async.bulk.commit_group;\ncp.async.bulk.wait_group 0;"
                                     ::"l"(P.s->part + ((b ^ (x << 1)) * 3 + x - 1) * 1024), "r"(sm + (10 + (hh ^ wq ^ 3)) * SLOT) : "memory");
                        marrive_n(BAR(B_SD), 2);
                        FENCE_ASYNC_G();
                    }
                    publish(e == 0 ? P.s->fh + ((3 - wq) * 1024 + tau * 32 + gg) : P.s->fp + ((b ^ (x << 1)) * 32 + x - 1), ep);
                }
                TS(88 + 2 * e + wq - 2);
            }
        }
    }
}

typedef CUresult (*EncodeFn)(CUtensorMap*, CUtensorMapDataType, cuuint32_t, void*, const cuuint64_t*, const cuuint64_t*, const cuuint32_t*,
                             const cuuint32_t*, CUtensorMapInterleave, CUtensorMapSwizzle, CUtensorMapL2promotion, CUtensorMapFloatOOBfill);

static void make_map(EncodeFn enc, CUtensorMap* m, const void* base, int rank, const cuuint64_t* dims, const cuuint64_t* strides,
                     const cuuint32_t* box, CUtensorMapSwizzle sw) {
    cuuint32_t es[3] = {1, 1, 1};
    enc(m, CU_TENSOR_MAP_DATA_TYPE_BFLOAT16, rank, (void*)base, dims, strides, box, es, CU_TENSOR_MAP_INTERLEAVE_NONE, sw,
        CU_TENSOR_MAP_L2_PROMOTION_L2_128B, CU_TENSOR_MAP_FLOAT_OOB_FILL_NONE);
}

extern "C" void kernel_launch(void* const* d_in, const int* in_sizes, int n_in, void* d_out, int out_size) {
    Params P;
    P.x = (const bf16*)d_in[0];
    for (int i = 0; i < 8; i++) P.par[i] = (const bf16*)d_in[1 + i];
    P.w1 = (const bf16*)d_in[10]; P.w2 = (const bf16*)d_in[11]; P.w3 = (const bf16*)d_in[12];
    P.w4 = (const bf16*)d_in[13]; P.c = (const bf16*)d_in[14]; P.wmod = (const bf16*)d_in[15]; P.out = (bf16*)d_out;

    void* fn = nullptr; cudaDriverEntryPointQueryResult qr;
    cudaGetDriverEntryPoint("cuTensorMapEncodeTiled", &fn, cudaEnableDefault, &qr);
    EncodeFn enc = (EncodeFn)fn;
    void* hbuf = nullptr; cudaGetSymbolAddress(&hbuf, g_s);
    P.s = (Scratch*)hbuf;
    Maps M;
    { cuuint64_t d[3] = {512, 256, 8}, s[2] = {8192, 1024}; cuuint32_t bx[3] = {8, 128, 4}; make_map(enc, &tmX, P.x, 3, d, s, bx, CU_TENSOR_MAP_SWIZZLE_NONE); }
    { cuuint64_t d[2] = {512, 512}, s[1] = {1024}; cuuint32_t bx[2] = {64, 128};
      make_map(enc, &tmW1, P.w1, 2, d, s, bx, CU_TENSOR_MAP_SWIZZLE_128B); make_map(enc, &tmW2, P.w2, 2, d, s, bx, CU_TENSOR_MAP_SWIZZLE_128B); }
    { cuuint64_t d[3] = {1792, 512, 2}, s[2] = {3584, 128}, sb[2] = {3584, 64}; cuuint32_t bx[3] = {64, 64, 2};
      make_map(enc, &tmW3, P.w3, 3, d, s, bx, CU_TENSOR_MAP_SWIZZLE_128B); make_map(enc, &tmW3b, P.w3, 3, d, sb, bx, CU_TENSOR_MAP_SWIZZLE_128B); }
    { cuuint64_t d[3] = {64, 1792, 8}, s[2] = {1024, 128}; cuuint32_t bx[3] = {64, 64, 2}, bh[3] = {64, 32, 2};
      make_map(enc, &tmW4, P.w4, 3, d, s, bx, CU_TENSOR_MAP_SWIZZLE_128B); make_map(enc, &tmW4h, P.w4, 3, d, s, bh, CU_TENSOR_MAP_SWIZZLE_128B); }
    { cuuint64_t d[3] = {512, 1028, 2}, s[2] = {1024, 1024 * 1024}; cuuint32_t bx[3] = {64, 32, 2}; make_map(enc, &tmH, hbuf, 3, d, s, bx, CU_TENSOR_MAP_SWIZZLE_128B); }
    { cuuint64_t d[3] = {4096, 2, 128}, s[2] = {8192, 16384}; cuuint32_t bx[3] = {128, 2, 32};
      make_map(enc, &tmX1, (char*)hbuf + offsetof(Scratch, x1), 3, d, s, bx, CU_TENSOR_MAP_SWIZZLE_NONE); }
    cudaFuncSetAttribute(fused_kernel, cudaFuncAttributeMaxDynamicSharedMemorySize, SMEM_BYTES);
    fused_kernel<<<128, 384, SMEM_BYTES, cudaStreamPerThread>>>(P, M);
}
```

```cpp
#include <cuda_runtime.h>
#include <cuda_bf16.h>
#include <cuda.h>
#include <stdint.h>
#include <stddef.h>

typedef __nv_bfloat16 bf16;
typedef unsigned long long u64;

struct Scratch {
    bf16     h[2052 * 512];
    uint4    z[32 * 8 * 512];
    bf16     xs[512 * 2048];
    uint4    hl[32 * 4 * 64];
    float2   zst[32 * 8 * 64];
    unsigned stats[2048];
    unsigned modp[8 * 3072];
    unsigned csum[8 * 1792];
    unsigned modf[3 * 512];
    unsigned f0[32], fh[32 * 32], fz[16 * 32], fb[32 * 32], epoch[128 * 32];
};
__device__ __align__(1024) Scratch g_s;
#define TS(i)

struct Params {
    const bf16* par[8];
    const bf16 *x, *wmod, *c;
    Scratch* s;
    const bf16 *w1, *w2, *w3, *w4;
    bf16* out;
};
struct Maps { CUtensorMap m[12]; };
#define tmX M.m[0]
#define tmW1 M.m[1]
#define tmW2 M.m[2]
#define tmW3 M.m[3]
#define tmW3b M.m[4]
#define tmW4 M.m[5]
#define tmW4h M.m[6]
#define tmH M.m[7]
#define tmXS M.m[8]
#define tmO M.m[11]
#define tmM M.m[9]

constexpr uint32_t SLOT = 16384;
constexpr uint32_t KST_P = 272, KST_W = 53 * 272, KP_P = 112;
constexpr uint32_t FT_CH = 3520, O_FT = 8 * SLOT - 4 * FT_CH;
constexpr uint32_t O_BOX = 8 * SLOT, BOX_CH = 12928, B5_O = 0, B3_O = 3200, B9_O = 6400, B7_O = 8576, B2_O = 10752;
constexpr uint32_t H2O = 1600, H3O = 1088;
constexpr uint32_t O_XG = O_BOX;
constexpr uint32_t O_U = O_BOX + 4 * BOX_CH, U_CH = 4480, U_H = 2240;
constexpr uint32_t O_NT = O_U + 4 * U_CH, NT_CH = 4496, NT_R = 280, NT_B = 2252;
constexpr uint32_t O_Y0 = O_NT + 4 * NT_CH, Y_CH = 2112;
constexpr uint32_t O_SV = (O_Y0 + 4 * Y_CH + 1023) / 1024 * 1024;
constexpr uint32_t O_T0 = (O_U + 1023) / 1024 * 1024, O_T1 = 4096, T_STRIDE = 14336;
constexpr uint32_t O_PAR = O_Y0, O_XR = O_XG + 32768;
constexpr uint32_t O_A = 8 * SLOT;
constexpr uint32_t O_BT = 13 * SLOT, O_VT = O_BT + 8192, O_GC = O_VT + 768, O_RC = O_GC + 80, O_RP = O_RC + 1024, O_HB = O_BT + 14336;
constexpr uint32_t O_BAR = 14 * SLOT, O_IC = O_BAR + 1056, O_GB = O_IC + 512, O_V4 = O_GB + 512, O_ML = O_V4 + 448;
static_assert(8 * KST_W <= O_FT && O_FT >= 7 * SLOT && 7 * KST_W + 32 * KP_P <= 7 * SLOT, "smem map");
constexpr u64 W3SLOT = 0x1A98DCA98DCA98DCull, W4SLOT = 0x320BDC761A9832DCull;
constexpr uint32_t SMEM_BYTES = 232448;
static_assert(O_SV + 1024 <= 14 * SLOT && O_ML + 68 <= SMEM_BYTES, "smem map");

enum {
    B_ZF = 0, B_W3 = 8, B_LH0 = 24, B_HP = 26,
    B_W2 = 30, B_W4 = 36,
    B_LH1 = 44,
    B_W1 = 46,
    B_J = 48,
    B_J0 = 49, B_HF = 50, B_XL = 58, B_XG = 62,
    B_KP = 64, B_TAB, B_CEND, B_DONE, B_PH, B_PZ, B_CR0, B_CR1, B_RP, B_E2 = 73, B_HS = 75, B_ZL = 76, B_ST = 77, B_T4 = 93, B_BA = 95, B_E1 = 96,
    B_U = 104, B_FAR = 106, B_MOD0 = 108, B_MOD1, B_BT, B_RC, B_V4, B_FB, B_FA, B_FO, B_SA, B_BS, B_CRA, B_XD, B_PZP, B_HB, B_PHP, B_HD,
    B_PAR = 128, B_XR
};

#define DI __device__ __forceinline__
#define SCHED_OPEN(v) uint32_t v; asm volatile("mov.u32 %0, %%clock;" : "=r"(v)::"memory")
#define SCHED_CLOSE(v) asm volatile("{\n.reg .u32 t;\nmov.u32 t, %%clock;\nst.shared.v2.u32 [%0], {t, %1};\n}" ::"r"(sm + O_ML + 64), "r"(v) : "memory")
#define SCHED_FENCE() asm volatile("{\n.reg .u32 t;\nmov.u32 t, %%clock;\nst.shared.u32 [%0], t;\n}" ::"r"(sm + O_ML + 64) : "memory")
template <int PH = 0> DI void mwait(uint32_t bar) {
    asm volatile("{\n.reg .pred p;\nWL: fence.mbarrier_init.release.cluster;\nmbarrier.try_wait.parity.shared::cta.b64 p, [%0], %1;\n@!p bra.uni WL;\n}" ::"r"(bar), "n"(PH) : "memory");
}
DI bool mtry(uint32_t bar) {
    uint32_t r; asm volatile("{\n.reg .pred p;\nmbarrier.test_wait.parity.shared::cta.b64 p, [%1], 0;\nselp.u32 %0, 1, 0, p;\n}" : "=r"(r) : "r"(bar) : "memory"); return r;
}
DI void mwaitb(uint32_t bar) {
    asm volatile("{\n.reg .pred p;\n.reg .u32 n;\nmov.u32 n, 0;\n"
                 "WL: mbarrier.try_wait.parity.shared::cta.b64 p, [%0], 0;\n@p bra.uni WD;\n"
                 "add.u32 n, n, 1;\nsetp.lt.u32 p, n, 2000000;\n@p bra.uni WL;\ntrap;\nWD:\n}" ::"r"(bar) : "memory");
}
DI bool elect() { uint32_t r; asm volatile("{\n.reg .pred p;\nelect.sync _|p, 0xffffffff;\nselp.u32 %0, 1, 0, p;\n}" : "=r"(r)); return r; }
DI void marrive_n(uint32_t bar, int n) { asm volatile("mbarrier.arrive.shared::cta.b64 _, [%0], %1;" ::"r"(bar), "r"(n) : "memory"); }
DI void marrive(uint32_t bar) { asm volatile("mbarrier.arrive.shared::cta.b64 _, [%0];" ::"r"(bar) : "memory"); }
DI void marrive_rem(uint32_t bar) { asm volatile("mbarrier.arrive.shared::cluster.b64 _, [%0];" ::"r"(bar) : "memory"); }
DI uint32_t mapa(uint32_t a, uint32_t r) { uint32_t o; asm("mapa.shared::cluster.u32 %0, %1, %2;" : "=r"(o) : "r"(a), "r"(r)); return o; }
DI void nbar(int id, int n) { asm volatile("bar.sync %0, %1;" ::"r"(id), "r"(n) : "memory"); }
DI uint32_t lds32(uint32_t a) { uint32_t v; asm volatile("ld.shared.u32 %0, [%1];" : "=r"(v) : "r"(a)); return v; }
DI uint32_t lds32v(uint32_t a) { uint32_t v; asm volatile("ld.volatile.shared.u32 %0, [%1];" : "=r"(v) : "r"(a)); return v; }
DI float ldsf(uint32_t a) { float v; asm volatile("ld.shared.f32 %0, [%1];" : "=f"(v) : "r"(a)); return v; }
DI uint2 lds64(uint32_t a) { uint2 v; asm volatile("ld.shared.v2.u32 {%0,%1}, [%2];" : "=r"(v.x), "=r"(v.y) : "r"(a)); return v; }
DI float2 ldsf2(uint32_t a) { float2 v; asm volatile("ld.shared.v2.f32 {%0,%1}, [%2];" : "=f"(v.x), "=f"(v.y) : "r"(a)); return v; }
DI uint4 lds128(uint32_t a) { uint4 v; asm volatile("ld.shared.v4.u32 {%0,%1,%2,%3}, [%4];" : "=r"(v.x), "=r"(v.y), "=r"(v.z), "=r"(v.w) : "r"(a)); return v; }
DI float4 ldsf4(uint32_t a) { float4 v; asm volatile("ld.shared.v4.f32 {%0,%1,%2,%3}, [%4];" : "=f"(v.x), "=f"(v.y), "=f"(v.z), "=f"(v.w) : "r"(a)); return v; }
DI void sts32(uint32_t a, uint32_t v) { asm volatile("st.shared.u32 [%0], %1;" ::"r"(a), "r"(v) : "memory"); }
DI void stsf(uint32_t a, float v) { asm volatile("st.shared.f32 [%0], %1;" ::"r"(a), "f"(v) : "memory"); }
DI void sts64(uint32_t a, uint32_t x, uint32_t y) { asm volatile("st.shared.v2.u32 [%0], {%1,%2};" ::"r"(a), "r"(x), "r"(y) : "memory"); }
DI void stsf2(uint32_t a, float x, float y) { asm volatile("st.shared.v2.f32 [%0], {%1,%2};" ::"r"(a), "f"(x), "f"(y) : "memory"); }
DI void sts128(uint32_t a, uint32_t x, uint32_t y, uint32_t z, uint32_t w) { asm volatile("st.shared.v4.u32 [%0], {%1,%2,%3,%4};" ::"r"(a), "r"(x), "r"(y), "r"(z), "r"(w) : "memory"); }
DI void stsf4(uint32_t a, float x, float y, float z, float w) { asm volatile("st.shared.v4.f32 [%0], {%1,%2,%3,%4};" ::"r"(a), "f"(x), "f"(y), "f"(z), "f"(w) : "memory"); }
DI void ldsm4(uint32_t a, uint32_t& r0, uint32_t& r1, uint32_t& r2, uint32_t& r3) {
    asm volatile("ldmatrix.sync.aligned.m8n8.x4.shared.b16 {%0,%1,%2,%3}, [%4];" : "=r"(r0), "=r"(r1), "=r"(r2), "=r"(r3) : "r"(a));
}
DI void ldsm4t(uint32_t a, uint32_t& r0, uint32_t& r1, uint32_t& r2, uint32_t& r3) {
    asm volatile("ldmatrix.sync.aligned.m8n8.x4.trans.shared.b16 {%0,%1,%2,%3}, [%4];" : "=r"(r0), "=r"(r1), "=r"(r2), "=r"(r3) : "r"(a));
}
DI void stsm4(uint32_t a, uint32_t r0, uint32_t r1, uint32_t r2, uint32_t r3) {
    asm volatile("stmatrix.sync.aligned.m8n8.x4.shared.b16 [%0], {%1,%2,%3,%4};" ::"r"(a), "r"(r0), "r"(r1), "r"(r2), "r"(r3) : "memory");
}
DI void stsm4t(uint32_t a, uint32_t r0, uint32_t r1, uint32_t r2, uint32_t r3) {
    asm volatile("stmatrix.sync.aligned.m8n8.x4.trans.shared.b16 [%0], {%1,%2,%3,%4};" ::"r"(a), "r"(r0), "r"(r1), "r"(r2), "r"(r3) : "memory");
}
DI void mma(float (&d)[4], uint32_t a0, uint32_t a1, uint32_t a2, uint32_t a3, uint32_t b0, uint32_t b1) {
    asm volatile("mma.sync.aligned.m16n8k16.row.col.f32.bf16.bf16.f32 {%0,%1,%2,%3}, {%4,%5,%6,%7}, {%8,%9}, {%0,%1,%2,%3};"
                 : "+f"(d[0]), "+f"(d[1]), "+f"(d[2]), "+f"(d[3]) : "r"(a0), "r"(a1), "r"(a2), "r"(a3), "r"(b0), "r"(b1));
}
DI uint32_t pk(float lo, float hi) { uint32_t r; asm("cvt.rn.bf16x2.f32 %0, %1, %2;" : "=r"(r) : "f"(hi), "f"(lo)); return r; }
DI float blo(uint32_t v) { return __uint_as_float(v << 16); }
DI float bhi(uint32_t v) { return __uint_as_float(v & 0xffff0000u); }
DI float rbf(float v) { return __bfloat162float(__float2bfloat16_rn(v)); }
DI uint4 ldg128(const void* p) { uint4 v; asm volatile("ld.global.nc.L1::no_allocate.v4.u32 {%0,%1,%2,%3}, [%4];" : "=r"(v.x), "=r"(v.y), "=r"(v.z), "=r"(v.w) : "l"(p)); return v; }
DI uint32_t ldg32(const void* p) { uint32_t v; asm volatile("ld.global.nc.u32 %0, [%1];" : "=r"(v) : "l"(p)); return v; }
DI unsigned short ldg16(const bf16* p) { unsigned short v; asm volatile("ld.global.nc.u16 %0, [%1];" : "=h"(v) : "l"(p)); return v; }
DI float b2f(unsigned short h) { float v; asm volatile("{\n.reg .b32 t;\ncvt.u32.u16 t, %1;\nshl.b32 %0, t, 16;\n}" : "=f"(v) : "h"(h)); return v; }
DI uint4 ldw128(const void* p) { uint4 v; asm volatile("ld.global.v4.u32 {%0,%1,%2,%3}, [%4];" : "=r"(v.x), "=r"(v.y), "=r"(v.z), "=r"(v.w) : "l"(p) : "memory"); return v; }
DI uint32_t ldw32(const void* p) { uint32_t v; asm volatile("ld.global.u32 %0, [%1];" : "=r"(v) : "l"(p) : "memory"); return v; }
DI float ldgbf(const bf16* p) { unsigned short v; asm volatile("ld.global.nc.u16 %0, [%1];" : "=h"(v) : "l"(p)); return __uint_as_float((uint32_t)v << 16); }
DI uint4 ldc128(const void* p) { uint4 v; asm volatile("ld.global.L1::no_allocate.v4.u32 {%0,%1,%2,%3}, [%4];" : "=r"(v.x), "=r"(v.y), "=r"(v.z), "=r"(v.w) : "l"(p) : "memory"); return v; }
DI uint2 ldc64(const void* p) { uint2 v; asm volatile("ld.global.L1::no_allocate.v2.u32 {%0,%1}, [%2];" : "=r"(v.x), "=r"(v.y) : "l"(p) : "memory"); return v; }
DI uint32_t ldc32(const void* p) { uint32_t v; asm volatile("ld.global.L1::no_allocate.u32 %0, [%1];" : "=r"(v) : "l"(p) : "memory"); return v; }
DI void stg128(void* p, uint4 v) { asm volatile("st.global.v4.u32 [%0], {%1,%2,%3,%4};" ::"l"(p), "r"(v.x), "r"(v.y), "r"(v.z), "r"(v.w) : "memory"); }
DI void st_rlx(unsigned* p, unsigned v) { asm volatile("st.relaxed.gpu.global.u32 [%0], %1;" ::"l"(p), "r"(v) : "memory"); }
DI void red_xor(unsigned* p, unsigned v) { asm volatile("red.relaxed.gpu.global.xor.b32 [%0], %1;" ::"l"(p), "r"(v) : "memory"); }
DI unsigned ld_rlx(const unsigned* p) { unsigned v; asm volatile("ld.relaxed.gpu.global.u32 %0, [%1];" : "=r"(v) : "l"(p) : "memory"); return v; }
DI void publish(unsigned* p) { asm volatile("red.release.gpu.global.add.u32 [%0], 1;" ::"l"(p) : "memory"); }
DI void poll(const unsigned* p, unsigned ep) {
    asm volatile("{\n.reg .pred p;\n.reg .u32 v;\n"
                 "PL: ld.acquire.gpu.global.u32 v, [%0];\nsetp.eq.u32 p, v, %1;\nvote.sync.all.pred p, p, 0xffffffff;\n@!p bra.uni PL;\n}" ::"l"(p), "r"(ep) : "memory");
}
DI unsigned pollb(const unsigned* p, unsigned ep, unsigned mask) {
    unsigned v;
    asm volatile("{\n.reg .pred p;\n.reg .u32 n, t;\nmov.u32 n, 0;\n"
                 "PL: ld.acquire.gpu.global.u32 %0, [%1];\nand.b32 t, %0, %3;\nsetp.eq.u32 p, t, %2;\nvote.sync.all.pred p, p, 0xffffffff;\n@p bra.uni PD;\n"
                 "add.u32 n, n, 1;\nsetp.lt.u32 p, n, 2000000;\n@p bra.uni PL;\ntrap;\nPD:\n}" : "=&r"(v) : "l"(p), "r"(ep), "r"(mask) : "memory");
    return v;
}
DI void tma2d(uint32_t dst, const CUtensorMap* m, int c0, int c1, uint32_t bar) {
    asm volatile("cp.async.bulk.tensor.2d.shared::cluster.global.mbarrier::complete_tx::bytes [%0], [%1, {%3,%4}], [%2];" ::"r"(dst), "l"(m), "r"(bar), "r"(c0), "r"(c1) : "memory");
}
DI void tma2d_mc(uint32_t dst, const CUtensorMap* m, int c0, int c1, uint32_t bar) {
    asm volatile("cp.async.bulk.tensor.2d.shared::cluster.global.mbarrier::complete_tx::bytes.multicast::cluster [%0], [%1, {%3,%4}], [%2], %5;" ::"r"(dst), "l"(m), "r"(bar), "r"(c0), "r"(c1), "h"((unsigned short)3) : "memory");
}
DI void tma3d(uint32_t dst, const CUtensorMap* m, int c0, int c1, int c2, uint32_t bar) {
    asm volatile("cp.async.bulk.tensor.3d.shared::cluster.global.mbarrier::complete_tx::bytes [%0], [%1, {%3,%4,%5}], [%2];" ::"r"(dst), "l"(m), "r"(bar), "r"(c0), "r"(c1), "r"(c2) : "memory");
}
DI void tma3d_mc(uint32_t dst, const CUtensorMap* m, int c0, int c1, int c2, uint32_t bar) {
    asm volatile("cp.async.bulk.tensor.3d.shared::cluster.global.mbarrier::complete_tx::bytes.multicast::cluster [%0], [%1, {%3,%4,%5}], [%2], %6;" ::"r"(dst), "l"(m), "r"(bar), "r"(c0), "r"(c1), "r"(c2), "h"((unsigned short)3) : "memory");
}
DI void bulk_ld(uint32_t dst, const void* src, uint32_t bytes, uint32_t bar) {
    asm volatile("cp.async.bulk.shared::cluster.global.mbarrier::complete_tx::bytes [%0], [%1], %2, [%3];" ::"r"(dst), "l"(src), "r"(bytes), "r"(bar) : "memory");
}
DI void bulk_ld_mc(uint32_t dst, const void* src, uint32_t bytes, uint32_t bar) {
    asm volatile("cp.async.bulk.shared::cluster.global.mbarrier::complete_tx::bytes.multicast::cluster [%0], [%1], %2, [%3], %4;" ::"r"(dst), "l"(src), "r"(bytes), "r"(bar), "h"((unsigned short)3) : "memory");
}
DI void l2_prefetch(const void* p, uint32_t bytes) { asm volatile("cp.async.bulk.prefetch.L2.global [%0], %1;" ::"l"(p), "r"(bytes) : "memory"); }
DI void st_async(uint32_t dst, const uint32_t (&v)[4], uint32_t bar) {
    asm volatile("st.async.shared::cluster.mbarrier::complete_tx::bytes.v4.b32 [%0], {%1,%2,%3,%4}, [%5];" ::"r"(dst), "r"(v[0]), "r"(v[1]), "r"(v[2]), "r"(v[3]), "r"(bar) : "memory");
}
#define FENCE_ASYNC_S() asm volatile("fence.proxy.async.shared::cta;" ::: "memory")
#define FENCE_ASYNC_G() asm volatile("fence.proxy.async.global;" ::: "memory")
#define WG_FENCE() asm volatile("wgmma.fence.sync.aligned;" ::: "memory")
#define WG_COMMIT() asm volatile("wgmma.commit_group.sync.aligned;" ::: "memory")
#define WG_WAIT(n) asm volatile("wgmma.wait_group.sync.aligned %0;" ::"n"(n) : "memory")
template <int N> DI void pin(float (&d)[N]) {
#pragma unroll
    for (int i = 0; i < N; i++) asm volatile("" : "+f"(d[i])::"memory");
}
constexpr uint32_t SM_BASE = 1024;
DI uint64_t mkdesc(uint32_t off16, uint32_t off, uint32_t lbo) {
    uint32_t lo = off16 + (((SM_BASE + off) >> 4) | ((lbo >> 4) << 16));
    uint64_t d; asm("mov.b64 %0, {%1, %2};" : "=l"(d) : "r"(lo), "r"(0x40000040u)); return d;
}
DI uint32_t hadd2(uint32_t a, uint32_t b) { uint32_t d; asm("add.rn.bf16x2 %0, %1, %2;" : "=r"(d) : "r"(a), "r"(b)); return d; }
DI uint32_t hmul2(uint32_t a, uint32_t b) { uint32_t d; asm("mul.rn.bf16x2 %0, %1, %2;" : "=r"(d) : "r"(a), "r"(b)); return d; }
DI uint32_t hfma2(uint32_t a, uint32_t b, uint32_t c) { uint32_t d; asm("fma.rn.bf16x2 %0, %1, %2, %3;" : "=r"(d) : "r"(a), "r"(b), "r"(c)); return d; }
DI void wgmma_n8(float (&d)[4], uint64_t da, uint64_t db, int sc) {
    asm volatile("{\n.reg .pred p;\nsetp.ne.b32 p, %6, 0;\nwgmma.mma_async.sync.aligned.m64n8k16.f32.bf16.bf16 {%0,%1,%2,%3}, %4, %5, p, 1, 1, 1, 0;\n}"
                 : "+f"(d[0]), "+f"(d[1]), "+f"(d[2]), "+f"(d[3]) : "l"(da), "l"(db), "r"(sc));
}
DI void wgmma_rs_n8(float (&d)[4], const uint32_t (&a)[4], uint64_t db, int sc) {
    asm volatile("{\n.reg .pred p;\nsetp.ne.b32 p, %9, 0;\nwgmma.mma_async.sync.aligned.m64n8k16.f32.bf16.bf16 {%0,%1,%2,%3}, {%4,%5,%6,%7}, %8, p, 1, 1, 0;\n}"
                 : "+f"(d[0]), "+f"(d[1]), "+f"(d[2]), "+f"(d[3]) : "r"(a[0]), "r"(a[1]), "r"(a[2]), "r"(a[3]), "l"(db), "r"(sc));
}
__device__ __forceinline__ void wgmma_ss_n64(float (&d)[32], uint64_t da, uint64_t db, int sc){
  asm volatile("{.reg .pred p; setp.ne.b32 p, %34, 0;\n wgmma.mma_async.sync.aligned.m64n64k16.f32.bf16.bf16 {%0,%1,%2,%3,%4,%5,%6,%7,%8,%9,%10,%11,%12,%13,%14,%15,%16,%17,%18,%19,%20,%21,%22,%23,%24,%25,%26,%27,%28,%29,%30,%31}, %32, %33, p, 1, 1, 0, 1;}\n"
   : "+f"(d[0]),"+f"(d[1]),"+f"(d[2]),"+f"(d[3]),"+f"(d[4]),"+f"(d[5]),"+f"(d[6]),"+f"(d[7]),"+f"(d[8]),"+f"(d[9]),"+f"(d[10]),"+f"(d[11]),"+f"(d[12]),"+f"(d[13]),"+f"(d[14]),"+f"(d[15]),"+f"(d[16]),"+f"(d[17]),"+f"(d[18]),"+f"(d[19]),"+f"(d[20]),"+f"(d[21]),"+f"(d[22]),"+f"(d[23]),"+f"(d[24]),"+f"(d[25]),"+f"(d[26]),"+f"(d[27]),"+f"(d[28]),"+f"(d[29]),"+f"(d[30]),"+f"(d[31])
   : "l"(da),"l"(db),"r"(sc));
}
__device__ __forceinline__ void wgmma_ss_n96(float (&d)[48], uint64_t da, uint64_t db, int sc){
  asm volatile("{.reg .pred p; setp.ne.b32 p, %50, 0;\n wgmma.mma_async.sync.aligned.m64n96k16.f32.bf16.bf16 {%0,%1,%2,%3,%4,%5,%6,%7,%8,%9,%10,%11,%12,%13,%14,%15,%16,%17,%18,%19,%20,%21,%22,%23,%24,%25,%26,%27,%28,%29,%30,%31,%32,%33,%34,%35,%36,%37,%38,%39,%40,%41,%42,%43,%44,%45,%46,%47}, %48, %49, p, 1, 1, 0, 1;}\n"
   : "+f"(d[0]),"+f"(d[1]),"+f"(d[2]),"+f"(d[3]),"+f"(d[4]),"+f"(d[5]),"+f"(d[6]),"+f"(d[7]),"+f"(d[8]),"+f"(d[9]),"+f"(d[10]),"+f"(d[11]),"+f"(d[12]),"+f"(d[13]),"+f"(d[14]),"+f"(d[15]),"+f"(d[16]),"+f"(d[17]),"+f"(d[18]),"+f"(d[19]),"+f"(d[20]),"+f"(d[21]),"+f"(d[22]),"+f"(d[23]),"+f"(d[24]),"+f"(d[25]),"+f"(d[26]),"+f"(d[27]),"+f"(d[28]),"+f"(d[29]),"+f"(d[30]),"+f"(d[31]),"+f"(d[32]),"+f"(d[33]),"+f"(d[34]),"+f"(d[35]),"+f"(d[36]),"+f"(d[37]),"+f"(d[38]),"+f"(d[39]),"+f"(d[40]),"+f"(d[41]),"+f"(d[42]),"+f"(d[43]),"+f"(d[44]),"+f"(d[45]),"+f"(d[46]),"+f"(d[47])
   : "l"(da),"l"(db),"r"(sc));
}
__device__ __forceinline__ void wgmma_ss_n128(float (&d)[64], uint64_t da, uint64_t db, int sc){
  asm volatile("{.reg .pred p; setp.ne.b32 p, %66, 0;\n wgmma.mma_async.sync.aligned.m64n128k16.f32.bf16.bf16 {%0,%1,%2,%3,%4,%5,%6,%7,%8,%9,%10,%11,%12,%13,%14,%15,%16,%17,%18,%19,%20,%21,%22,%23,%24,%25,%26,%27,%28,%29,%30,%31,%32,%33,%34,%35,%36,%37,%38,%39,%40,%41,%42,%43,%44,%45,%46,%47,%48,%49,%50,%51,%52,%53,%54,%55,%56,%57,%58,%59,%60,%61,%62,%63}, %64, %65, p, 1, 1, 0, 1;}\n"
   : "+f"(d[0]),"+f"(d[1]),"+f"(d[2]),"+f"(d[3]),"+f"(d[4]),"+f"(d[5]),"+f"(d[6]),"+f"(d[7]),"+f"(d[8]),"+f"(d[9]),"+f"(d[10]),"+f"(d[11]),"+f"(d[12]),"+f"(d[13]),"+f"(d[14]),"+f"(d[15]),"+f"(d[16]),"+f"(d[17]),"+f"(d[18]),"+f"(d[19]),"+f"(d[20]),"+f"(d[21]),"+f"(d[22]),"+f"(d[23]),"+f"(d[24]),"+f"(d[25]),"+f"(d[26]),"+f"(d[27]),"+f"(d[28]),"+f"(d[29]),"+f"(d[30]),"+f"(d[31]),"+f"(d[32]),"+f"(d[33]),"+f"(d[34]),"+f"(d[35]),"+f"(d[36]),"+f"(d[37]),"+f"(d[38]),"+f"(d[39]),"+f"(d[40]),"+f"(d[41]),"+f"(d[42]),"+f"(d[43]),"+f"(d[44]),"+f"(d[45]),"+f"(d[46]),"+f"(d[47]),"+f"(d[48]),"+f"(d[49]),"+f"(d[50]),"+f"(d[51]),"+f"(d[52]),"+f"(d[53]),"+f"(d[54]),"+f"(d[55]),"+f"(d[56]),"+f"(d[57]),"+f"(d[58]),"+f"(d[59]),"+f"(d[60]),"+f"(d[61]),"+f"(d[62]),"+f"(d[63])
   : "l"(da),"l"(db),"r"(sc));
}
__device__ __forceinline__ void wgmma_rs_n64(float (&d)[32], const uint32_t (&a)[4], uint64_t db, int sc){
  asm volatile("{.reg .pred p; setp.ne.b32 p, %37, 0;\n wgmma.mma_async.sync.aligned.m64n64k16.f32.bf16.bf16 {%0,%1,%2,%3,%4,%5,%6,%7,%8,%9,%10,%11,%12,%13,%14,%15,%16,%17,%18,%19,%20,%21,%22,%23,%24,%25,%26,%27,%28,%29,%30,%31}, {%32,%33,%34,%35}, %36, p, 1, 1, 1;}\n"
   : "+f"(d[0]),"+f"(d[1]),"+f"(d[2]),"+f"(d[3]),"+f"(d[4]),"+f"(d[5]),"+f"(d[6]),"+f"(d[7]),"+f"(d[8]),"+f"(d[9]),"+f"(d[10]),"+f"(d[11]),"+f"(d[12]),"+f"(d[13]),"+f"(d[14]),"+f"(d[15]),"+f"(d[16]),"+f"(d[17]),"+f"(d[18]),"+f"(d[19]),"+f"(d[20]),"+f"(d[21]),"+f"(d[22]),"+f"(d[23]),"+f"(d[24]),"+f"(d[25]),"+f"(d[26]),"+f"(d[27]),"+f"(d[28]),"+f"(d[29]),"+f"(d[30]),"+f"(d[31])
   : "r"(a[0]),"r"(a[1]),"r"(a[2]),"r"(a[3]),"l"(db),"r"(sc));
}
__device__ __forceinline__ void wgmma_rs_n128(float (&d)[64], const uint32_t (&a)[4], uint64_t db, int sc){
  asm volatile("{.reg .pred p; setp.ne.b32 p, %69, 0;\n wgmma.mma_async.sync.aligned.m64n128k16.f32.bf16.bf16 {%0,%1,%2,%3,%4,%5,%6,%7,%8,%9,%10,%11,%12,%13,%14,%15,%16,%17,%18,%19,%20,%21,%22,%23,%24,%25,%26,%27,%28,%29,%30,%31,%32,%33,%34,%35,%36,%37,%38,%39,%40,%41,%42,%43,%44,%45,%46,%47,%48,%49,%50,%51,%52,%53,%54,%55,%56,%57,%58,%59,%60,%61,%62,%63}, {%64,%65,%66,%67}, %68, p, 1, 1, 1;}\n"
   : "+f"(d[0]),"+f"(d[1]),"+f"(d[2]),"+f"(d[3]),"+f"(d[4]),"+f"(d[5]),"+f"(d[6]),"+f"(d[7]),"+f"(d[8]),"+f"(d[9]),"+f"(d[10]),"+f"(d[11]),"+f"(d[12]),"+f"(d[13]),"+f"(d[14]),"+f"(d[15]),"+f"(d[16]),"+f"(d[17]),"+f"(d[18]),"+f"(d[19]),"+f"(d[20]),"+f"(d[21]),"+f"(d[22]),"+f"(d[23]),"+f"(d[24]),"+f"(d[25]),"+f"(d[26]),"+f"(d[27]),"+f"(d[28]),"+f"(d[29]),"+f"(d[30]),"+f"(d[31]),"+f"(d[32]),"+f"(d[33]),"+f"(d[34]),"+f"(d[35]),"+f"(d[36]),"+f"(d[37]),"+f"(d[38]),"+f"(d[39]),"+f"(d[40]),"+f"(d[41]),"+f"(d[42]),"+f"(d[43]),"+f"(d[44]),"+f"(d[45]),"+f"(d[46]),"+f"(d[47]),"+f"(d[48]),"+f"(d[49]),"+f"(d[50]),"+f"(d[51]),"+f"(d[52]),"+f"(d[53]),"+f"(d[54]),"+f"(d[55]),"+f"(d[56]),"+f"(d[57]),"+f"(d[58]),"+f"(d[59]),"+f"(d[60]),"+f"(d[61]),"+f"(d[62]),"+f"(d[63])
   : "r"(a[0]),"r"(a[1]),"r"(a[2]),"r"(a[3]),"l"(db),"r"(sc));
}

struct C2 { float r, i; };
DI C2 cmul(C2 a, C2 b) { C2 o; o.r = fmaf(a.r, b.r, -a.i * b.i); o.i = fmaf(a.r, b.i, a.i * b.r); return o; }
DI C2 cpow(float a2, float th, float l) {
    float m; asm("ex2.approx.ftz.f32 %0, %1;" : "=f"(m) : "f"(a2 * l));
    float ph = th * l; ph -= rintf(ph); ph *= 6.283185307179586f;
    C2 o; o.r = m * __cosf(ph); o.i = m * __sinf(ph); return o;
}
constexpr float GK0 = 0.7978845608028654f, GK1 = 0.044715f;
DI uint32_t gelu_tail(uint32_t y, uint32_t A, uint32_t B) {
    uint32_t u = hmul2(y, hfma2(hmul2(y, y), A, B)), t;
    asm("tanh.approx.bf16x2 %0, %1;" : "=r"(t) : "r"(u));
    return hfma2(y, t, y);
}
DI void row_stats(float s, float q, float& mu, float& r, float eps = 1e-5f) {
    mu = s * (1.f / 512);
    asm("rsqrt.approx.ftz.f32 %0, %1;" : "=f"(r) : "f"(fmaxf(q * (1.f / 512) - mu * mu, 0.f) + eps));
}
struct RowC { uint32_t nmu, A, B; };
DI RowC rowc(float mu, float r) { RowC c; float B = GK0 * r, A = GK1 * B * r * r; c.nmu = pk(-mu, -mu); c.A = pk(A, A); c.B = pk(B, B); return c; }
template <int N> DI void gelu16(const float (&acc)[N], int i, uint32_t vaddr, const RowC& lo, const RowC& hi, uint32_t (&o)[4]) {
    uint2 v = lds64(vaddr);
    o[0] = gelu_tail(hfma2(v.x, lo.nmu, pk(acc[8 * i + 0], acc[8 * i + 1])), lo.A, lo.B);
    o[1] = gelu_tail(hfma2(v.x, hi.nmu, pk(acc[8 * i + 2], acc[8 * i + 3])), hi.A, hi.B);
    o[2] = gelu_tail(hfma2(v.y, lo.nmu, pk(acc[8 * i + 4], acc[8 * i + 5])), lo.A, lo.B);
    o[3] = gelu_tail(hfma2(v.y, hi.nmu, pk(acc[8 * i + 6], acc[8 * i + 7])), hi.A, hi.B);
}
template <int N> DI void gelu16a(const float (&acc)[N], int i, uint2 v, const RowC& lo, const RowC& hi, uint32_t (&y)[4], uint32_t (&u)[4]) {
    y[0] = hfma2(v.x, lo.nmu, pk(acc[8 * i + 0], acc[8 * i + 1])); y[1] = hfma2(v.x, hi.nmu, pk(acc[8 * i + 2], acc[8 * i + 3]));
    y[2] = hfma2(v.y, lo.nmu, pk(acc[8 * i + 4], acc[8 * i + 5])); y[3] = hfma2(v.y, hi.nmu, pk(acc[8 * i + 6], acc[8 * i + 7]));
#pragma unroll
    for (int k = 0; k < 4; k++) u[k] = hmul2(y[k], hfma2(hmul2(y[k], y[k]), (k & 1) ? hi.A : lo.A, (k & 1) ? hi.B : lo.B));
}
DI void gelu16b(const uint32_t (&y)[4], const uint32_t (&u)[4], uint32_t (&o)[4]) {
#pragma unroll
    for (int k = 0; k < 4; k++) { uint32_t t; asm("tanh.approx.bf16x2 %0, %1;" : "=r"(t) : "r"(u[k])); o[k] = hfma2(y[k], t, y[k]); }
}
DI float qsum(float v) { v += __shfl_xor_sync(~0u, v, 1); v += __shfl_xor_sync(~0u, v, 2); return v; }
DI void ln_rows(const uint4 (&v)[4], int lane, unsigned* dst, unsigned ep) {
    float s[2], q[2];
#pragma unroll
    for (int r = 0; r < 2; r++) {
        s[r] = 0.f; q[r] = 0.f;
#pragma unroll
        for (int j = 0; j < 2; j++) {
            uint32_t w[4] = {v[2 * r + j].x, v[2 * r + j].y, v[2 * r + j].z, v[2 * r + j].w};
#pragma unroll
            for (int k = 0; k < 4; k++) { float a = blo(w[k]), c = bhi(w[k]); s[r] += a + c; q[r] = fmaf(a, a, fmaf(c, c, q[r])); }
        }
    }
    bool u = lane & 16;
    float ss = (u ? s[1] : s[0]) + __shfl_xor_sync(~0u, u ? s[0] : s[1], 16);
    float qq = (u ? q[1] : q[0]) + __shfl_xor_sync(~0u, u ? q[0] : q[1], 16);
#pragma unroll
    for (int o = 8; o; o >>= 1) { ss += __shfl_xor_sync(~0u, ss, o); qq += __shfl_xor_sync(~0u, qq, o); }
    float mu, r; row_stats(ss, qq, mu, r); r = rbf(r);
    if ((lane & 15) == 0) red_xor(dst, pk(-mu * r, r) | 0x80000000u);
}
template <int W> DI void conv_near(float (&acc)[8][4], uint32_t ua, uint32_t n1, uint32_t n2) {
#pragma unroll(W ? 2 : 4)
    for (int r = 0; r < 8; r++) {
        uint32_t u[12][2];
#pragma unroll
        for (int i = 5; i >= (W ? 0 : 2); i--) ldsm4(ua + i * 256, u[2 * i][0], u[2 * i][1], u[2 * i + 1][0], u[2 * i + 1][1]);
#pragma unroll
        for (int q = 0; q < 5; q++) {
            if (q < 4 || r < 2) {
                const uint2 a = lds64(n1 + q * 64), e = lds64(n2 + q * 64);
#pragma unroll
                for (int j = 7; j >= (W ? 0 : q); j--) mma(acc[j], a.x, a.y, e.x, e.y, u[j - q + 4][0], u[j - q + 4][1]);
            }
        }
        ua -= 16; n1 += 8; n2 += 8;
    }
}
template <int W> DI void conv_far(float (&acc)[8][4], uint32_t bx, int ph, uint32_t ft) {
#pragma unroll
    for (int gi = 0; gi < 4; gi++) {
        const uint32_t aa = bx + ((gi & 1) ? B5_O : B3_O) + ((gi >> 1) ? (ph ^ 1) * (H2O - 16) : ph * H2O);
        uint32_t a[6][4]; uint2 f[6];
#pragma unroll
        for (int k = 0; k < (W ? 6 : 2); k++) ldsm4t(aa + k * 256, a[k][0], a[k][1], a[k][2], a[k][3]);
#pragma unroll
        for (int i = 0; i < (W ? 6 : 4); i++) f[i] = lds64(ft + gi * 448 + i * 64);
#pragma unroll
        for (int t = 0; t < 3; t++)
#pragma unroll
            for (int j = 7; j >= 0; j--) {
                const int k = (j >> 1) + 4 * W - 2 - t, i = 2 * t + (j & 1);
                if (k >= 0) mma(acc[j], a[k][0], a[k][1], a[k][2], a[k][3], f[i].x, f[i].y);
            }
    }
    if (W) {
#pragma unroll
        for (int gi = 0; gi < 3; gi++) {
            const uint32_t aa = bx + B9_O + gi * 2176 + (gi == 0 ? (ph ^ 1) * (H3O - 16) : ph * H3O);
            uint32_t a[4][4]; uint2 f[8];
#pragma unroll
            for (int k = 0; k < 4; k++) ldsm4t(aa + k * 256, a[k][0], a[k][1], a[k][2], a[k][3]);
#pragma unroll
            for (int i = 0; i < (gi < 2 ? 8 : 2); i++) f[i] = lds64(ft + 1792 + gi * 576 + i * 64);
#pragma unroll
            for (int t = 0; t < (gi < 2 ? 4 : 1); t++)
#pragma unroll
                for (int j = 7; j >= 2 * t; j--) {
                    const int k = (j >> 1) - t, i = 2 * t + (j & 1);
                    mma(acc[j], a[k][0], a[k][1], a[k][2], a[k][3], f[i].x, f[i].y);
                }
        }
    }
}

__global__ void __launch_bounds__(384, 1) __cluster_dims__(2, 1, 1)
fused_kernel(const __grid_constant__ Params P, const __grid_constant__ Maps M) {
    extern __shared__ __align__(1024) unsigned char smem_raw[];
    const uint32_t sm = (uint32_t)__cvta_generic_to_shared(smem_raw);
    const int ba = blockIdx.x;
    if (threadIdx.x < 64) {
        const int i = threadIdx.x >> 3;
        asm volatile("prefetch.global.L2 [%0];" ::"l"(P.par[i] + (i < 6 ? ba * 512 + (threadIdx.x & 7) * 64 : ba * 4)));
    }
    const uint32_t bars = sm + O_BAR;
#define ZG(u) (((gg ^ ((u) >> 1)) & 1) + 2 * ((u) & 1))
#define BAR(i) (bars + 8u * (uint32_t)(i))
#define WARRIVE_N(i, n) do { __syncwarp(); if (lane == 0) marrive_n(BAR(i), n); } while (0)
#define WARRIVE(i) do { __syncwarp(); if (lane == 0) marrive(BAR(i)); } while (0)
    const int cl = blockIdx.x >> 1, cb = cl - 36, col = cl < 4 ? 0 : cl < 36 ? (cl - 4) & 7 : cb % 7 + 1, row = cl < 4 ? 4 + cl : cl < 36 ? (cl - 4) >> 3 : 4 + cb / 7;
    const int b = (row * 2 + (col & 1)) * 8 + (col >> 1) * 2 + (blockIdx.x & 1), tid = __shfl_xor_sync(~0u, ((int)threadIdx.x - 128) ^ 129, 1), lane = tid & 31;
    const int warp = __shfl_sync(~0u, (((int)threadIdx.x - 128) ^ 128) >> 5, 0), wg = warp >> 2, wq = warp & 3, t128 = tid & 127;
    const int g = lane >> 2, c = lane & 3;
    const int p = b & 1, kq = (b >> 1) & 3, hh = kq >> 1, gg = 2 * p + (kq & 1), tau = 2 * (b >> 3) + hh, fj = b & 7;

    if (wg >= 0) {
        const int ch = wq;
        unsigned ep;
        float dskip;
        {
            if (warp == 0 && elect()) {
                asm volatile("mbarrier.init.shared::cta.b64 [%0], 1;\nmbarrier.init.shared::cta.b64 [%0+8], 1;\n"
                             "mbarrier.arrive.expect_tx.shared::cta.b64 _, [%0], 6176;\nmbarrier.arrive.expect_tx.shared::cta.b64 _, [%0+8], 16384;\n"
                             "fence.mbarrier_init.release.cluster;" ::"r"(BAR(B_PAR)) : "memory");
#pragma unroll
                for (int i = 0; i < 6; i++) bulk_ld(sm + O_PAR + i * 1024, P.par[i] + ba * 512, 1024, BAR(B_PAR));
#pragma unroll
                for (int i = 0; i < 2; i++) bulk_ld(sm + O_PAR + 6144 + i * 16, P.par[6 + i] + (ba >> 1) * 8, 16, BAR(B_PAR));
                bulk_ld(sm + O_XR, P.x + ba * 8192, 16384, BAR(B_XR));
            }
            if (warp == 0) TS(53);
            ep = ld_rlx(P.s->epoch + (ba * 32 + lane));
            asm volatile("barrier.cluster.arrive.relaxed.aligned;" ::: "memory");
#pragma unroll
            for (int i = 0; i < 5; i++) sts128(sm + O_NT + (i < 4 ? i * 4096 : 4 * NT_CH - 4096) + tid * 16, 0, 0, 0, 0);
#pragma unroll
            for (int i = 0; i < 4; i++) sts128(sm + O_FT + (i < 3 ? i * 4096 : 4 * FT_CH - 4096) + tid * 16, 0, 0, 0, 0);
            asm volatile("barrier.cluster.wait.aligned;" ::: "memory");
            if (warp == 1 && elect()) {
                tma3d(sm + O_XG + p * 8192, &tmX, 8 * (ba >> 1), 0, 4 * p, BAR(B_XL));
                tma3d(sm + O_XG + 16384 + p * 8192, &tmX, 8 * (ba >> 1), 128, 4 * p, BAR(B_XL + 1));
            }
            if (warp == 0) TS(64);
            mwait(BAR(B_PAR));
            if (warp == 0) TS(61);
            const uint32_t pa = sm + O_PAR + ch * 256 + wg * 128 + lane * 4, pb = sm + O_PAR + 6144 + p * 8 + (ch >> 1) * 4;
            const uint32_t r_ldt = lds32(pb), r_are = lds32(pa), r_aim = lds32(pa + 1024), r_bre = lds32(pa + 2048), r_bim = lds32(pa + 3072),
                           r_cre = lds32(pa + 4096), r_cim = lds32(pa + 5120), r_dk = lds32(pb + 16);
            unsigned* stp = P.s->stats + ((wq >> 1) * 1024 + 8 * ba + 4 * wg + 2 * (wq & 1) + (lane >> 4));
            if ((lane & 15) == 0) st_rlx(stp, ep << 31);
            dskip = (ch & 1) ? bhi(r_dk) : blo(r_dk);
            const float dt = rbf(expf((ch & 1) ? bhi(r_ldt) : blo(r_ldt)));
            const uint32_t kst = sm + warp * KST_W, ka = kst + lane * 8;
            C2 w8[2], z1[2], h2[2], f[2], f2[2], f4[2], f6[2], a[2];
#pragma unroll
            for (int m = 0; m < 2; m++) {
                C2 B = {m ? bhi(r_bre) : blo(r_bre), m ? bhi(r_bim) : blo(r_bim)}, C = {m ? bhi(r_cre) : blo(r_cre), m ? bhi(r_cim) : blo(r_cim)};
                C2 cb = cmul(C, B); f[m].r = cb.r * dt; f[m].i = -cb.i * dt; a[m] = f[m];
            }
#define LNPOS 0
#define KSTORE(row, v) sts64(ka + (row) * KST_P, pk(v[0].r, v[0].i), pk(v[1].r, v[1].i))
#define KMUL(o, x, y) do { o[0] = cmul(x[0], y[0]); o[1] = cmul(x[1], y[1]); } while (0)
            KSTORE(32, f);
#pragma unroll
            for (int m = 0; m < 2; m++) {
                float a2 = dt * (m ? bhi(r_are) : blo(r_are)) * 1.4426950408889634f;
                float th = dt * (m ? bhi(r_aim) : blo(r_aim)) * 0.15915494309189535f;
                w8[m] = cpow(a2, th, 8.f); z1[m] = cpow(a2, -th, 1.f); h2[m] = cpow(a2, -th, 256.f);
            }
            KMUL(f, f, z1); KSTORE(33, f); KMUL(f2, f, z1); KSTORE(34, f2); KMUL(f, f2, z1); KSTORE(35, f);
            KMUL(f4, f, z1); KSTORE(36, f4); KMUL(f, f4, z1); KSTORE(37, f); KMUL(f6, f, z1); KSTORE(38, f6);
            KMUL(f, f6, z1); KSTORE(39, f);
            KMUL(f2, f2, h2); KSTORE(41, f2); KMUL(f6, f6, h2); KSTORE(43, f6);
            KMUL(a, a, h2); KSTORE(40, a); KMUL(f4, f4, h2); KSTORE(42, f4);
            KMUL(a, a, h2); KSTORE(44, a); KMUL(f4, f4, h2); KSTORE(45, f4);
            KMUL(a, a, h2); KSTORE(46, a); KMUL(f4, f4, h2); KSTORE(47, f4);
#pragma unroll 1
            for (int r = 48; r < 53; r++) { KMUL(a, a, h2); KSTORE(r, a); }
            {
                uint32_t pa[3][2], pb[3][2];
                KMUL(f, w8, w8); KMUL(f, f, f); KMUL(f, f, f); KMUL(f2, f, f); KMUL(f4, f2, f);
#pragma unroll
                for (int m = 0; m < 2; m++) {
                    pa[0][m] = pk(f[m].r, f[m].i); pb[0][m] = pk(-f[m].i, f[m].r); pa[1][m] = pk(f2[m].r, f2[m].i); pb[1][m] = pk(-f2[m].i, f2[m].r);
                    pa[2][m] = pk(f4[m].r, f4[m].i); pb[2][m] = pk(-f4[m].i, f4[m].r);
                }
                a[0] = C2{1.f, 0.f}; a[1] = a[0];
#pragma unroll 2
                for (int r = 0; r < 8; r++) {
                    const uint32_t q0 = pk(a[0].r, a[0].i), q1 = pk(a[1].r, a[1].i);
                    KMUL(a, a, w8);
                    sts64(ka + r * KST_P, q0, q1);
#pragma unroll
                    for (int i = 0; i < 3; i++)
                        sts64(ka + (r + 8 * i + 8) * KST_P, hfma2(__byte_perm(q0, 0, 0x1010), pa[i][0], hmul2(__byte_perm(q0, 0, 0x3232), pb[i][0])),
                              hfma2(__byte_perm(q1, 0, 0x1010), pa[i][1], hmul2(__byte_perm(q1, 0, 0x3232), pb[i][1])));
                }
            }
            if (warp == 0) TS(62);
            ep++;
            mwait(BAR(B_XR));
            uint4 xa[4];
#pragma unroll
            for (int i = 0; i < 4; i++) xa[i] = lds128(sm + O_XR + warp * 2048 + i * 512 + lane * 16);
            __syncwarp();
            ln_rows(xa, lane, stp, ep);
            SCHED_FENCE();
            float d[6][4];
#pragma unroll
            for (int i = 0; i < 6; i++) { d[i][0] = d[i][1] = d[i][2] = d[i][3] = 0.f; }
            const uint32_t aA = kst + (lane & 15) * KST_P + (lane >> 4) * 16;
            const uint32_t aB = kst + (32 + 8 * (lane >> 4) + (lane & 7)) * KST_P + ((lane >> 3) & 1) * 16;
            const uint32_t aC = kst + (48 + (lane & 7)) * KST_P + (lane >> 3) * 16;
#pragma unroll
            for (int k2 = 0; k2 < 4; k2++) {
                uint32_t t0, t1, t2, t3; ldsm4(aC + k2 * 64, t0, t1, t2, t3);
#pragma unroll
                for (int e = 0; e < 2; e++) {
                    uint32_t x0, x1, x2, x3, y0, y1, y2, y3, b0, b1, b2, b3;
                    ldsm4(aA + k2 * 64 + e * 32, x0, x1, x2, x3); ldsm4(aA + 16 * KST_P + k2 * 64 + e * 32, y0, y1, y2, y3);
                    ldsm4(aB + k2 * 64 + e * 32, b0, b1, b2, b3);
                    mma(d[0], x0, x1, x2, x3, b0, b1); mma(d[1], x0, x1, x2, x3, b2, b3); mma(d[2], x0, x1, x2, x3, e ? t2 : t0, e ? t3 : t1);
                    mma(d[3], y0, y1, y2, y3, b0, b1); mma(d[4], y0, y1, y2, y3, b2, b3); mma(d[5], y0, y1, y2, y3, e ? t2 : t0, e ? t3 : t1);
                }
            }
            __syncwarp();
#pragma unroll
            for (int i = 0; i < 6; i++) {
                uint32_t o = kst + ((i / 3) * 16 + g) * KP_P + (i % 3) * 32 + c * 8;
                stsf2(o, d[i][0], d[i][1]); stsf2(o + 8 * KP_P, d[i][2], d[i][3]);
            }
            WARRIVE(B_KP);
            if (warp == 0) TS(1);
        }
        uint32_t xt[4][4];
        float acc0[8][4];
        const int ph = (lane >> 3) & 1, mr = 8 * (lane >> 4) + (lane & 7), o = g - 2 * c;
        const uint32_t ua = sm + O_U + ch * U_CH + ph * U_H + (64 * wg - 24 + mr) * 16;
        const uint32_t na = sm + O_NT + ch * NT_CH + (o & 7) * NT_R, n1 = na + (o < 0 ? NT_B + 4 : 8), n2 = na + (o < 0 ? 0 : NT_B + 4);
        {
            uint2 xr[8];
            uint32_t st[8], bad;
            uint4 mc;
            mwait(BAR(B_XL + wg)); mwait(BAR(B_XG + wg));
#pragma unroll
            for (int j = 0; j < 8; j++) xr[j] = lds64(sm + O_XG + wg * 16384 + j * 2048 + t128 * 16 + p * 8);
            if (t128 == 0) asm volatile("mbarrier.arrive.shared::cluster.b64 _, [%0], 2;" ::"r"(mapa(BAR(B_XD), p ^ 1)) : "memory");
            if (wq == 0) TS(4 + wg);
            bool first = true;
            do {
#pragma unroll
                for (int j = 0; j < 2; j++)
                    asm volatile("ld.relaxed.gpu.global.v4.u32 {%0,%1,%2,%3}, [%4];" : "=r"(st[4 * j]), "=r"(st[4 * j + 1]), "=r"(st[4 * j + 2]), "=r"(st[4 * j + 3])
                                 : "l"(P.s->stats + (1024 * j + 4 * tid)) : "memory");
                if (first) {
                    first = false;
                    mwait(BAR(B_KP));
                    const uint32_t k0 = sm + ch * KST_W, k1 = k0 + 4 * KST_W, nt = sm + O_NT + ch * NT_CH + (2 + 32 * wg + lane) * 4;
                    float v[8], pv;
                    if (wg == 0) {
                        float4 p0 = ldsf4(k0 + lane * KP_P), p1 = ldsf4(k0 + lane * KP_P + 16), q0 = ldsf4(k1 + lane * KP_P), q1 = ldsf4(k1 + lane * KP_P + 16);
                        v[0] = p0.x + q0.x; v[1] = p0.y + q0.y; v[2] = p0.z + q0.z; v[3] = p0.w + q0.w;
                        v[4] = p1.x + q1.x; v[5] = p1.y + q1.y; v[6] = p1.z + q1.z; v[7] = p1.w + q1.w;
                        pv = __shfl_up_sync(~0u, v[7], 1);
                        if (lane == 0) { pv = 0.f; v[0] += dskip; }
                    } else {
                        float4 p0 = ldsf4(k0 + lane * KP_P + 32), q0 = ldsf4(k1 + lane * KP_P + 32);
                        uint32_t eo = lane == 0 ? 31 * KP_P + 28 : 48;
                        float ex = ldsf(k0 + eo) + ldsf(k1 + eo);
                        v[0] = v[1] = p0.x + q0.x; v[2] = p0.y + q0.y; v[3] = v[4] = v[5] = p0.z + q0.z; v[6] = p0.w + q0.w;
                        v[7] = __shfl_down_sync(~0u, v[0], 1); if (lane == 31) v[7] = ex;
                        pv = lane == 0 ? ex : v[0];
                        if (lane >= 24)
                            sts32(sm + O_NT + ch * NT_CH + 66 * 4 + c * NT_R + (g & 1) * NT_B, pk(c == 3 ? 0.f : ex, ex));
                    }
#pragma unroll
                    for (int i = 0; i < 8; i++) { const uint32_t t = pk(v[i], i ? v[i - 1] : pv); sts32(nt + i * NT_R, t); sts32(nt + i * NT_R + NT_B, t); }
                    if (wq == 0) TS(2 + wg);
#pragma unroll
                    for (int j = 0; j < 4; j++) {
                        xt[0][j] = __byte_perm(xr[2 * j].x, xr[2 * j + 1].x, 0x5410); xt[1][j] = __byte_perm(xr[2 * j].x, xr[2 * j + 1].x, 0x7632);
                        xt[2][j] = __byte_perm(xr[2 * j].y, xr[2 * j + 1].y, 0x5410); xt[3][j] = __byte_perm(xr[2 * j].y, xr[2 * j + 1].y, 0x7632);
                    }
#pragma unroll
                    for (int j = 0; j < 8; j++) { acc0[j][0] = acc0[j][1] = acc0[j][2] = acc0[j][3] = 0.f; }
                    mwait(BAR(B_MOD0));
                    if (wq == 0) TS(8 + wg);
                    mc = lds128(sm + O_ML);
                    if (wg == 0) sts128(sm + O_U + (2 * wq + (lane >> 4)) * U_H + (lane & 7) * 16, 0, 0, 0, 0);
                }
                bad = 0;
#pragma unroll
                for (int j = 0; j < 8; j++) { st[j] ^= ep << 31; bad |= st[j]; }
            } while (__any_sync(~0u, (int)bad < 0));
            if (wq == 0) TS(6 + wg);
            const uint32_t uo = sm + O_U + (t128 & 1) * U_H + (8 + 64 * wg + (t128 >> 1)) * 16;
            uint32_t r2[4], nm2[4];
#pragma unroll
            for (int j = 0; j < 4; j++) { r2[j] = __byte_perm(st[2 * j], st[2 * j + 1], 0x7632); nm2[j] = __byte_perm(st[2 * j], st[2 * j + 1], 0x5410); }
#pragma unroll
            for (int k = 0; k < 4; k++) {
                const uint32_t sel = (k & 1) ? 0x3232 : 0x1010, sa = __byte_perm((k & 2) ? mc.y : mc.x, 0, sel), c1 = __byte_perm((k & 2) ? mc.w : mc.z, 0, sel);
                sts128(uo + k * U_CH, hfma2(hfma2(xt[k][0], r2[0], nm2[0]), c1, sa), hfma2(hfma2(xt[k][1], r2[1], nm2[1]), c1, sa),
                       hfma2(hfma2(xt[k][2], r2[2], nm2[2]), c1, sa), hfma2(hfma2(xt[k][3], r2[3], nm2[3]), c1, sa));
            }
            WARRIVE(B_TAB);
        }
        {
            float (&acc)[8][4] = acc0;
            const uint32_t bx = sm + O_BOX + ch * BOX_CH + (mr + 1) * 16, ft = sm + O_FT + ch * FT_CH + (8 + o) * 8;
            nbar(3, 256);
            if (wg) {
                if (wq == 0) TS(11);
                conv_near<1>(acc, ua, n1, n2);
                if (wq == 0) TS(13);
                mwait(BAR(B_FAR + 1));
                if (wq == 0) TS(15);
                conv_far<1>(acc, bx, ph, ft);
            } else {
                if (wq == 0) TS(10);
                conv_near<0>(acc, ua, n1, n2);
                if (wq == 0) TS(12);
                mwait(BAR(B_FAR));
                if (wq == 0) TS(14);
                conv_far<0>(acc, bx, ph, ft);
            }
            if (wq == 0) TS(16 + wg);
            const uint32_t yb = wg ? sm + O_BOX + B9_O : sm + O_Y0, ych = wg ? BOX_CH : Y_CH;
            __syncwarp();
#pragma unroll
            for (int j = 0; j < 8; j += 2)
                stsm4t(yb + ch * ych + ph * H3O + (8 * j + mr) * 16, pk(acc[j][0], acc[j][1]), pk(acc[j][2], acc[j][3]),
                       pk(acc[j + 1][0], acc[j + 1][1]), pk(acc[j + 1][2], acc[j + 1][3]));
            mwait(BAR(B_MOD1));
            const uint4 gc = lds128(sm + O_ML + 16);
            nbar(1 + wg, 128);
            uint4 yq[4];
#pragma unroll
            for (int k = 0; k < 4; k++) yq[k] = lds128(yb + k * ych + (t128 & 1) * H3O + (t128 >> 1) * 16);
#pragma unroll
            for (int k = 0; k < 4; k++) {
                const uint32_t sel = (k & 1) ? 0x3232 : 0x1010, ga = __byte_perm((k & 2) ? gc.y : gc.x, 0, sel), c1 = __byte_perm((k & 2) ? gc.w : gc.z, 0, sel);
                stg128(P.s->xs + ((4 * ba + k) * 2048 + 8 * tid), make_uint4(hmul2(hfma2(ga, yq[k].x, xt[k][0]), c1), hmul2(hfma2(ga, yq[k].y, xt[k][1]), c1),
                                                                             hmul2(hfma2(ga, yq[k].z, xt[k][2]), c1), hmul2(hfma2(ga, yq[k].w, xt[k][3]), c1)));
            }
            if (wq == 0) TS(66 + wg);
            WARRIVE(B_CEND);
        }
        const uint32_t swz0 = sm + warp * 2048 + (lane & 15) * 128 + (((lane >> 4) ^ (lane & 7)) << 4);
#define SWZ(q) (swz0 ^ ((q) << 5))
        const uint32_t swt = sm + (8 * (lane >> 4) + (lane & 7)) * 128 + (((2 * wq + ((lane >> 3) & 1)) ^ (lane & 7)) << 4);
        uint32_t xs[16];
        float zac[32];
        if (wg == 0) {
            {
                uint32_t m[3][4], bad;
                do {
                    bad = 0;
#pragma unroll
                    for (int i = 0; i < 3; i++)
                        asm volatile("ld.relaxed.gpu.global.v4.u32 {%0,%1,%2,%3}, [%4];" : "=r"(m[i][0]), "=r"(m[i][1]), "=r"(m[i][2]), "=r"(m[i][3]) : "l"(P.s->modf + (512 * i + 4 * t128)) : "memory");
#pragma unroll
                    for (int i = 0; i < 12; i++) bad |= m[i >> 2][i & 3] ^ (ep | 0x80u);
                } while (__any_sync(~0u, bad & 0xffu));
                float ic[4];
#pragma unroll
                for (int i = 0; i < 4; i++) asm("rcp.approx.ftz.f32 %0, %1;" : "=f"(ic[i]) : "f"(bhi(m[1][i])));
                const uint32_t i0 = pk(ic[0], ic[1]), i1 = pk(ic[2], ic[3]), q0 = pk(ic[0] * ic[0], ic[1] * ic[1]), q1 = pk(ic[2] * ic[2], ic[3] * ic[3]), one = 0x3f803f80u;
                if (wq == gg) stsf4(sm + O_IC + lane * 16, ic[0], ic[1], ic[2], ic[3]);
                if ((wq >> 1) == p) {
                    const uint32_t a = sm + O_GB + (wq & 1) * 256 + (lane >> 2) * 32 + (lane & 1) * 16 + (lane & 2) * 2;
                    sts32(a, __byte_perm(m[2][0], m[2][1], 0x7632)); sts32(a + 8, __byte_perm(m[2][2], m[2][3], 0x7632));
                }
                float gs[5] = {0.f, 0.f, 0.f, 0.f, 0.f};
#pragma unroll
                for (int i = 0; i < 4; i++) {
                    const float cv = bhi(m[1][i]), sv = bhi(m[0][i]);
                    gs[0] += cv; gs[1] += sv; gs[2] = fmaf(cv, cv, gs[2]); gs[3] = fmaf(cv, sv, gs[3]); gs[4] = fmaf(sv, sv, gs[4]);
                }
#pragma unroll 1
                for (int d = 16; d; d >>= 1)
#pragma unroll
                    for (int i = 0; i < 5; i++) gs[i] += __shfl_xor_sync(~0u, gs[i], d);
                const uint32_t a = (sm + O_BT + (t128 >> 4) * 1024 + (t128 & 15) * 8);
                if (wq == 0) TS(18);
                mwait(BAR(B_CEND));
                stsf4(sm + O_GC + wq * 16, gs[0], gs[1], gs[2], gs[3]); stsf(sm + O_GC + 64 + wq * 4, gs[4]);
                sts64(a, i0, i1); sts64((a + 128) ^ 16, one, one);
                sts64((a + 256) ^ 32, __byte_perm(m[1][0], m[1][1], 0x7632), __byte_perm(m[1][2], m[1][3], 0x7632));
                sts64((a + 384) ^ 48, __byte_perm(m[0][0], m[0][1], 0x7632), __byte_perm(m[0][2], m[0][3], 0x7632));
                sts64((a + 512) ^ 64, q0, q1); sts64((a + 640) ^ 80, one, one);
                FENCE_ASYNC_S();
                WARRIVE(B_BT);
            }
        }
        {
            float d[4];
            mwait(BAR(B_BT)); mwait(BAR(B_W1 + wg));
#pragma unroll 1
            for (int s = 0; s < 4; s++) {
                WG_FENCE();
#pragma unroll
                for (int k = 0; k < 8; k++) wgmma_n8(d, mkdesc(wg * 4096 + s * 1024, k * 2048, 16), mkdesc(s * 128, O_BT + (k >> 2) * 1024 + (k & 3) * 32, 16), s | k);
                WG_COMMIT();
            }
            WG_WAIT(0); pin(d);
            const uint32_t a = O_VT + warp * 32 + (g >> 1) * 8 + (g & 1) * 2;
            if (c < 2) { *(bf16*)(smem_raw + a + 512 - 256 * c) = __float2bfloat16_rn(d[1]); *(bf16*)(smem_raw + a + 516 - 256 * c) = __float2bfloat16_rn(d[3]); }
            if (c == 1) { *(bf16*)(smem_raw + a) = __float2bfloat16_rn(d[0]); *(bf16*)(smem_raw + a + 4) = __float2bfloat16_rn(d[2]); }
            nbar(1 + wg, 128);
            if (warp == 4) TS(20);
        }
        {
            uint2 v1[4], v2[4], v3[4];
#pragma unroll
            for (int q = 0; q < 4; q++) { const uint32_t a = sm + O_VT + wg * 128 + q * 32 + c * 8; v1[q] = lds64(a); v2[q] = lds64(a + 256); v3[q] = lds64(a + 512); }
            float acc[32], dl[4], dq[4];
            uint32_t af[2][4][4];
#pragma unroll 1
            for (int s = 0; s < 2; s++) {
#pragma unroll
                for (int e = 0; e < 2; e++) {
                    uint32_t sq[4][4];
                    const int kb = 4 * wg + 2 * s + e;
                    mwait(BAR(B_HF + kb));
                    if (warp == 0 && s == 0 && e == 0) TS(22);
#pragma unroll
                    for (int k = 0; k < 4; k++) ldsm4t(swt + O_A + kb * 8192 + k * 2048, af[e][k][0], af[e][k][1], af[e][k][2], af[e][k][3]);
#pragma unroll
                    for (int k = 0; k < 16; k++) sq[k >> 2][k & 3] = hmul2(af[e][k >> 2][k & 3], af[e][k >> 2][k & 3]);
                    WG_FENCE();
#pragma unroll
                    for (int k = 0; k < 4; k++) { wgmma_rs_n8(dl, af[e][k], mkdesc(kb * 64, O_BT + k * 32, 16), s | e | k); wgmma_rs_n8(dq, sq[k], mkdesc(kb * 64, O_BT + k * 32, 16), s | e | k); }
                    WG_COMMIT();
#pragma unroll
                    for (int k = 0; k < 4; k++) wgmma_rs_n64(acc, af[e][k], mkdesc(wg * 4096 + kb * 512, k * 2048, 16), s | e | k);
                    WG_COMMIT();
                    if (s) { mwait(BAR(B_HF + 4 * (wg ^ 1) + 2 * e)); mwait(BAR(B_HF + 4 * (wg ^ 1) + 2 * e + 1)); }
                    WG_WAIT(1);
                    if (s == 1 && e == 0 && lane == 0) marrive_n(BAR(B_E1 + wg), 2);
                }
            }
            pin(dl); pin(dq);
            uint32_t ag[16][4];
            {
                const uint32_t a = sm + O_RP + (16 * warp + g) * 32 + c * 8;
                stsf2(a, c < 2 ? dl[0] : dq[0], c < 2 ? dl[1] : dq[1]); stsf2(a + 256, c < 2 ? dl[2] : dq[2], c < 2 ? dl[3] : dq[3]);
            }
            WARRIVE(B_RP);
#pragma unroll
            for (int k = 0; k < 8; k++) ldsm4t(swt + O_A + (wg ^ 1) * 32768 + k * 2048, ag[k][0], ag[k][1], ag[k][2], ag[k][3]);
#pragma unroll
            for (int s = 0; s < 2; s++) {
                WG_FENCE();
#pragma unroll
                for (int k = 0; k < 8; k++) wgmma_rs_n64(acc, ag[8 * s + k], mkdesc(2048 + wg * 2048, s * SLOT + k * 2048, 16), 1);
                WG_COMMIT();
                if (s == 0) {
#pragma unroll
                    for (int k = 8; k < 16; k++) ldsm4t(swt + O_A + (wg ^ 1) * 32768 + k * 2048, ag[k][0], ag[k][1], ag[k][2], ag[k][3]);
                }
                WG_WAIT(1);
                if (lane == 0) marrive_n(BAR(B_E1 + 2 + 2 * s + wg), 2);
            }
            mwait(BAR(B_RC));
            const uint4 c0 = lds128(sm + O_RC + (16 * wq + g) * 16), c1 = lds128(sm + O_RC + (16 * wq + g + 8) * 16);
            const float al0 = __uint_as_float(c0.x), al1 = __uint_as_float(c1.x);
            const uint32_t y0 = c0.y, y1 = c1.y, z0 = c0.z, z1 = c1.z, w0 = c0.w, w1 = c1.w;
            const uint32_t kA = pk(GK1 / (GK0 * GK0), GK1 / (GK0 * GK0)), kB = 0x3f803f80u;
            uint2 cr[2][4];
#pragma unroll
            for (int e = 0; e < 1; e++) {
                const uint32_t a1 = __byte_perm(e ? y1 : y0, 0, 0x1010), a2 = __byte_perm(e ? y1 : y0, 0, 0x3232), a3 = __byte_perm(e ? z1 : z0, 0, 0x1010);
#pragma unroll
                for (int q = 0; q < 4; q++) { cr[e][q].x = hfma2(v2[q].x, a2, hfma2(v1[q].x, a1, hmul2(v3[q].x, a3))); cr[e][q].y = hfma2(v2[q].y, a2, hfma2(v1[q].y, a1, hmul2(v3[q].y, a3))); }
            }
            bf16* ho = P.s->h + ((64 * tau + 16 * wq + (lane >> 3) + 2) * 512 + 128 * gg + 64 * wg + (lane & 7) * 8);
            SCHED_OPEN(ck1);
            WG_WAIT(0); pin(acc);
            if (warp == 0) TS(23);
            if (lane == 0) marrive_n(BAR(B_E1 + 6 + wg), 2);
#pragma unroll
            for (int q = 0; q < 4; q++) ldsm4t(swt + O_A + (2 * gg + wg) * 8192 + q * 2048, xs[4 * q], xs[4 * q + 1], xs[4 * q + 2], xs[4 * q + 3]);
#define H1PAIR(q, f, i) gelu_tail(hadd2(cr[e][q].f, pk(acc[8 * (q) + (i)] * al, acc[8 * (q) + (i) + 1] * al)), kA, kB)
            const uint32_t stg = sm + 12 * SLOT + warp * 2048;
#pragma unroll
            for (int e = 0; e < 2; e++) {
                const float al = e ? al1 : al0;
                const uint32_t sa = stg + e * 1024 + (lane & 7) * 128 + (((lane >> 3) ^ (lane & 7)) << 4);
                stsm4(sa, H1PAIR(0, x, 2 * e), H1PAIR(0, y, 4 + 2 * e), H1PAIR(1, x, 2 * e), H1PAIR(1, y, 4 + 2 * e));
                stsm4(sa ^ 64, H1PAIR(2, x, 2 * e), H1PAIR(2, y, 4 + 2 * e), H1PAIR(3, x, 2 * e), H1PAIR(3, y, 4 + 2 * e));
                if (e) FENCE_ASYNC_S();
                __syncwarp();
                const uint32_t la = stg + e * 1024 + (lane >> 3) * 128 + (((lane & 7) ^ (lane >> 3)) << 4);
                const uint4 t0 = lds128(la), t1 = lds128((la + 512) ^ 64);
                if (e != (gg & 1) && wq == 3 * e && (lane >> 4) == e) {
                    const uint4 t = e ? t1 : t0;
                    asm volatile("{\n.reg .b64 a, b;\nmov.b64 a, {%1, %5};\nmov.b64 b, {%2, %5};\nst.relaxed.gpu.global.v2.b64 [%0], {a, b};\n"
                                 "mov.b64 a, {%3, %5};\nmov.b64 b, {%4, %5};\nst.relaxed.gpu.global.v2.b64 [%0+16], {a, b};\n}"
                                 ::"l"(P.s->hl + ((tau * 4 + gg) * 64 + (lane & 8) * 4 + wg * 16 + (lane & 7) * 2)), "r"(t.x), "r"(t.y), "r"(t.z), "r"(t.w), "r"(ep) : "memory");
                }
                stg128(ho + e * 4096, t0); stg128(ho + e * 4096 + 2048, t1);
                if (e == 0) {
                SCHED_CLOSE(ck1);
#pragma unroll
            for (int e = 1; e < 2; e++) {
                const uint32_t a1 = __byte_perm(e ? y1 : y0, 0, 0x1010), a2 = __byte_perm(e ? y1 : y0, 0, 0x3232), a3 = __byte_perm(e ? z1 : z0, 0, 0x1010);
#pragma unroll
                for (int q = 0; q < 4; q++) { cr[e][q].x = hfma2(v2[q].x, a2, hfma2(v1[q].x, a1, hmul2(v3[q].x, a3))); cr[e][q].y = hfma2(v2[q].y, a2, hfma2(v1[q].y, a1, hmul2(v3[q].y, a3))); }
            }
                }
            }
            WARRIVE(B_PH);
            if (warp == 0) TS(25);
#pragma unroll
            for (int n = 0; n < 8; n++) {
                const uint32_t a = sm + O_BT + (2 * gg + wg) * 1024 + c * 4, cv = lds32(a + 256 + ((n ^ 2) << 4)), sv = lds32(a + 384 + ((n ^ 3) << 4));
                const uint32_t h0 = hfma2(xs[2 * n], __byte_perm(z0, 0, 0x3232), hfma2(cv, __byte_perm(w0, 0, 0x1010), sv));
                const uint32_t h1 = hfma2(xs[2 * n + 1], __byte_perm(z1, 0, 0x3232), hfma2(cv, __byte_perm(w1, 0, 0x1010), sv));
                zac[4 * n] = blo(h0) * (2.f * GK0); zac[4 * n + 1] = bhi(h0) * (2.f * GK0); zac[4 * n + 2] = blo(h1) * (2.f * GK0); zac[4 * n + 3] = bhi(h1) * (2.f * GK0);
            }
            SCHED_FENCE();
        }
        asm volatile("setmaxnreg.inc.sync.aligned.u32 232;");
        {
#pragma unroll
            for (int s = 0; s < 2; s++) {
                const int r = 16 * wq + (lane & 15) + ((gg & 1) ? 1 + (p ^ s) : -1 - (p ^ s));
                const bool in = (unsigned)r < 64u;
                const uint32_t a0 = in ? sm + (s ? O_A : 12 * SLOT) + r * 128 + (((lane >> 4) ^ (r & 7)) << 4) : sm + O_HB + s * 512 + (r & 1) * 256 + (lane & 16);
                const uint32_t a1 = a0 + (in ? 8192 : 128);
                uint32_t af[8][4];
                mwait(BAR(B_W2 + s)); mwait(BAR(B_HB)); mwait(BAR(s ? B_HP : B_PH));
                if (warp == 0) TS(29 + s);
#pragma unroll
                for (int k = 0; k < 8; k++) ldsm4((k < 4 ? a0 : a1) ^ ((k & 3) << 5), af[k][0], af[k][1], af[k][2], af[k][3]);
                WG_FENCE();
#pragma unroll
                for (int k = 0; k < 8; k++) wgmma_rs_n64(zac, af[k], mkdesc(wg * 6144 + s * 1024, k * 2048, 16), 1);
                WG_COMMIT();
                if (s == 0) WG_WAIT(0);
            }
            if (lane == 0) { marrive(BAR(B_E2)); if (wg) marrive_rem(mapa(BAR(B_HD), p ^ 1)); }
#pragma unroll 1
            for (int s = 2; s < 4; s++) {
                mwait(BAR(B_W2 + s));
#pragma unroll
                for (int e = 0; e < 2; e++) {
                    const int kb = 2 * s + (e ^ p);
                    mwait<1>(BAR(B_HF + kb));
                    if (wq == 0 && s == 2 && e == 0) TS(27 + wg);
                    WG_FENCE();
#pragma unroll
                    for (int k = 0; k < 4; k++)
                        wgmma_ss_n64(zac, mkdesc(kb * 512, O_A + k * 32, 16), mkdesc(wg * 2048 + kb * 512, k * 2048, 16), 1);
                }
                WG_COMMIT();
            }
            WG_WAIT(1);
            if (lane == 0) marrive(BAR(B_E2 + 1));
            mwait(BAR(B_E2));
            uint4* zo = P.s->z + ((tau * 8 + 2 * gg) * 512 + warp * 128 + lane);
            WG_WAIT(0); pin(zac);
            if (wq == 0) TS(31 + wg);
#pragma unroll
            for (int q = 0; q < 4; q++)
                stsm4(SWZ(q), pk(zac[8 * q], zac[8 * q + 1]), pk(zac[8 * q + 2], zac[8 * q + 3]), pk(zac[8 * q + 4], zac[8 * q + 5]), pk(zac[8 * q + 6], zac[8 * q + 7]));
            __syncwarp();
            uint4 t[4];
#pragma unroll
            for (int k = 0; k < 4; k++) t[k] = lds128(sm + warp * 2048 + k * 512 + lane * 16);
#pragma unroll
            for (int k = 0; k < 4; k++) stg128(zo + 32 * k, t[k]);
            SCHED_FENCE();
            float s0 = 0.f, q0 = 0.f, s1 = 0.f, q1 = 0.f;
#pragma unroll
            for (int n = 0; n < 8; n++) {
                s0 += zac[4 * n] + zac[4 * n + 1]; q0 = fmaf(zac[4 * n], zac[4 * n], fmaf(zac[4 * n + 1], zac[4 * n + 1], q0));
                s1 += zac[4 * n + 2] + zac[4 * n + 3]; q1 = fmaf(zac[4 * n + 2], zac[4 * n + 2], fmaf(zac[4 * n + 3], zac[4 * n + 3], q1));
            }
            { const bool u = c & 1;
              s0 = (u ? s1 : s0) + __shfl_xor_sync(~0u, u ? s0 : s1, 1); q0 = (u ? q1 : q0) + __shfl_xor_sync(~0u, u ? q0 : q1, 1);
              s0 += __shfl_xor_sync(~0u, s0, 2); q0 += __shfl_xor_sync(~0u, q0, 2); }
            if (c < 2) P.s->zst[(tau * 8 + 2 * gg) * 64 + 16 * warp + g + 8 * c] = make_float2(s0, q0);
            WARRIVE(B_PZ);
            if (wq == 0) TS(33 + wg);
            mwait(BAR(B_PZ));
            if (wg == 0 && lane == 0) marrive_rem(mapa(BAR(B_PZP), p ^ 1));
#pragma unroll
            for (int q = 0; q < 4; q++)
                stsm4(SWZ(q) + (2 * p + hh) * SLOT, pk(zac[8 * q], zac[8 * q + 1]), pk(zac[8 * q + 2], zac[8 * q + 3]), pk(zac[8 * q + 4], zac[8 * q + 5]), pk(zac[8 * q + 6], zac[8 * q + 7]));
            FENCE_ASYNC_S();
            WARRIVE(B_ZL);
#pragma unroll
            for (int q = 0; q < 4; q++) {
                const uint2 gv = lds64(sm + O_GB + (gg & 1) * 256 + wg * 128 + q * 32 + c * 8);
                uint32_t o[4];
#pragma unroll
                for (int e = 0; e < 2; e++) {
                    const float2 ic = ldsf2(sm + O_IC + wg * 256 + q * 64 + e * 32 + c * 8);
                    const float g0 = blo(e ? gv.y : gv.x) * (0.5f / GK0), g1 = bhi(e ? gv.y : gv.x) * (0.5f / GK0);
#pragma unroll
                    for (int r = 0; r < 2; r++)
                        o[2 * e + r] = pk(fmaf(g0, zac[8 * q + 4 * e + 2 * r], blo(xs[4 * q + 2 * e + r]) * ic.x), fmaf(g1, zac[8 * q + 4 * e + 2 * r + 1], bhi(xs[4 * q + 2 * e + r]) * ic.y));
                }
                stsm4(SWZ(q) + 11 * SLOT, o[0], o[1], o[2], o[3]);
            }
            FENCE_ASYNC_S();
            WARRIVE(B_BA);
        }
        uint32_t Ho[14][4], Hp[14][4];
        float acc[64];
        uint32_t rp0, rp1, po[32];
        const uint32_t peer = p ^ 1;
#define W3A(i) ((uint32_t)((W3SLOT >> (4 * (i))) & 15) * SLOT)
#define W4A(i) ((uint32_t)((W4SLOT >> (4 * (i))) & 15) * SLOT)
#define G4PAIR(j, H, k0, first) do { \
            if (j) mwait(BAR(B_W4 + (j) / 2)); \
            WG_FENCE(); \
            _Pragma("unroll") \
            for (int k = 0; k < (((j) & 4) ? 6 : 8); k++) { \
                wgmma_rs_n128(acc, H[(k0) + k], mkdesc(0, W4A((j) + (k >> 2)) + (k & 3) * 2048, (((j) & 4) && k >= 4) ? 4096 : 8192), !(first) || k); \
                if (((j) & 7) == 6 && k == 3) WG_COMMIT(); } \
            WG_COMMIT(); } while (0)
#define G4PACK() _Pragma("unroll") for (int i = 0; i < 32; i++) po[i] = pk(acc[2 * i], acc[2 * i + 1])
        {
            float acc2[48];
            const float2* zs = P.s->zst + (((tau & ~1) + wg) * 512 + c * 128 + 16 * wq + g);
#define G3STEP(s) do { \
                mwait(BAR(B_W3 + (s))); mwait(BAR(((s) & 6) + wg == 2 * p + hh ? B_ZL : B_ZF + ((s) & 6) + wg)); \
                if (wq == 0 && (s) == 0) TS(35 + wg); \
                WG_FENCE(); \
                _Pragma("unroll") \
                for (int k = 0; k < 4; k++) \
                    wgmma_ss_n128(acc, mkdesc((((s) & 6) + wg) * 1024 + ((s) & 1) * 512, k * 32, 16), mkdesc((((uint32_t)W3SLOT >> (4 * (s))) & 15) * 1024, k * 2048, 8192), (s) | k); \
                WG_COMMIT(); \
                WG_WAIT(1); \
                if ((s) > 0 && lane == 0) marrive(BAR(B_ST + (s) - 1)); } while (0)
#pragma unroll 1
            for (int s = 0; s < 6; s++) G3STEP(s);
            const uint2 t0 = ldc64(zs), t1 = ldc64(zs + 64), t2 = ldc64(zs + 8), t3 = ldc64(zs + 72);
            const uint32_t va = sm + O_V4 + c * 8;
            uint2 vv[8]; uint32_t gy[2][4], gu[2][4];
#pragma unroll
            for (int s = 0; s < 8; s++) vv[s] = lds64(va + s * 32);
            G3STEP(6);
            SCHED_OPEN(ck0);
            float m0, m1, rs0, rs1;
            row_stats(qsum(__uint_as_float(t0.x) + __uint_as_float(t1.x)), qsum(__uint_as_float(t0.y) + __uint_as_float(t1.y)), m0, rs0, 1e-5f * 4.f * GK0 * GK0);
            row_stats(qsum(__uint_as_float(t2.x) + __uint_as_float(t3.x)), qsum(__uint_as_float(t2.y) + __uint_as_float(t3.y)), m1, rs1, 1e-5f * 4.f * GK0 * GK0);
            const RowC lo = rowc(m0, rs0), hi = rowc(m1, rs1);
            rp0 = pk(0.5f * rs0, 0.5f * rs0); rp1 = pk(0.5f * rs1, 0.5f * rs1);
            SCHED_CLOSE(ck0);
            G3STEP(7);
            const uint32_t l0 = mapa(sm + wg * 8192 + t128 * 16, peer), lb0 = mapa(BAR(wg), peer);
#define HOFF(k) ((k) < 4 ? 11 * SLOT + (k) * 2048 : (k) < 8 ? ((k) - 4) * 2048 : (k) < 12 ? 4 * SLOT + ((k) - 8) * 2048 : 5 * SLOT + ((k) - 12) * 2048)
#define HSEND(k) st_async(l0 + HOFF(k), Ho[k], lb0 + 8 * ((k) < 8 ? B_LH0 : B_LH1))
#pragma unroll
            for (int s = 0; s < 8; s++) {
                if (s == 0) mwait(BAR(B_W3 + 8));
                WG_FENCE();
#pragma unroll
                for (int k = 0; k < 4; k++)
                    wgmma_ss_n96(acc2, mkdesc(wg * 1024, (s & 6) * SLOT + (s & 1) * 8192 + k * 32, 16), mkdesc(0, W3A(8 + s) + k * 2048, 8192 + 64), s | k);
                WG_COMMIT();
                WG_WAIT(1);
                if (lane == 0) { marrive(BAR(B_ST + 7 + s)); if (s == 2 || s == 6) marrive_rem(mapa(BAR(s == 2 ? B_CR0 : B_CR1), peer)); }
                if (s == 0) { pin(acc); if (wq == 0) TS(37 + wg); gelu16a(acc, 0, vv[0], lo, hi, gy[0], gu[0]); }
                const bool rdy = mtry(BAR(s < 7 ? B_W3 + 9 + s : B_W4));
                if (s == 1) mwait(BAR(B_CRA));
                if (s == 5) mwait(BAR(B_CR0));
                if (s) HSEND(s - 1);
                SCHED_OPEN(ck);
                gelu16b(gy[s & 1], gu[s & 1], Ho[s]);
                if (s < 7) gelu16a(acc, s + 1, vv[(s + 1) & 7], lo, hi, gy[(s + 1) & 1], gu[(s + 1) & 1]);
                SCHED_CLOSE(ck);
                if (!rdy) mwait(BAR(s < 7 ? B_W3 + 9 + s : B_W4));
                if (warp == 0 && (s == 3 || s == 4)) TS(s == 3 ? 65 : 75);
            }
            G4PAIR(0, Ho, 0, 1);
            WG_WAIT(1); pin(acc2);
            if (wq == 0) TS(39 + wg);
            if (lane == 0) marrive(BAR(B_ST + 15));
#pragma unroll
            for (int k = 0; k < 6; k++) vv[k] = lds64(va + 256 + k * 32);
            mwait(BAR(B_CR1));
#define GELU2(k) do { HSEND(7 + (k)); SCHED_OPEN(ck); gelu16a(acc2, k, vv[k], lo, hi, gy[0], gu[0]); gelu16b(gy[0], gu[0], Ho[8 + (k)]); asm volatile("" ::"r"(ck)); cks ^= ck; } while (0)
            uint32_t cks = 0;
            GELU2(0); GELU2(1); GELU2(2);
            mwait(BAR(B_LH0 + wg));
#pragma unroll
            for (int k = 0; k < 8; k++) { uint4 t = lds128(sm + wg * 8192 + HOFF(k) + t128 * 16); Hp[k][0] = t.x; Hp[k][1] = t.y; Hp[k][2] = t.z; Hp[k][3] = t.w; }
            SCHED_FENCE();
            G4PAIR(2, Hp, 0, 0);
            WG_WAIT(1);
            if (lane == 0) marrive(BAR(B_T4));
            GELU2(3); GELU2(4); GELU2(5);
            SCHED_CLOSE(cks);
            if (wq == 0) TS(41 + wg);
            G4PAIR(4, Ho, 8, 0);
            HSEND(13);
        }
        WG_WAIT(1);
        if (lane == 0) marrive(BAR(B_T4 + 1));
        mwait(BAR(B_LH1 + wg));
#pragma unroll
        for (int k = 8; k < 14; k++) { uint4 t = lds128(sm + wg * 8192 + HOFF(k) + t128 * 16); Hp[k][0] = t.x; Hp[k][1] = t.y; Hp[k][2] = t.z; Hp[k][3] = t.w; }
        const int fs = wg ^ hh;
        if (fs) mwait(BAR(B_FA));
        G4PAIR(6, Hp, 8, 0);
        WG_WAIT(1);
        if (!fs && lane == 0) marrive(BAR(B_FA));
        mwait(BAR(B_BS));
        FENCE_ASYNC_G();
        WG_WAIT(0); pin(acc);
        if (wq == 0) TS(43 + fs);
        if (fs && lane == 0) marrive(BAR(B_SA));
        G4PACK();
#define G4HALF(ck, so, h) do { \
            uint2 gv[4]; \
            _Pragma("unroll") for (int q = 0; q < 4; q++) gv[q] = lds64(sm + O_GB + ((ck) & 1) * 256 + c * 8 + (h) * 128 + q * 32); \
            _Pragma("unroll") for (int q = 0; q < 4; q++) \
                stsm4(SWZ(q) + ((so) + (h)) * SLOT, hmul2(po[16 * (h) + 4 * q], hmul2(gv[q].x, rp0)), hmul2(po[16 * (h) + 4 * q + 1], hmul2(gv[q].x, rp1)), \
                      hmul2(po[16 * (h) + 4 * q + 2], hmul2(gv[q].y, rp0)), hmul2(po[16 * (h) + 4 * q + 3], hmul2(gv[q].y, rp1))); } while (0)
#define G4RED(ck, so) do { \
            FENCE_ASYNC_S(); \
            __syncwarp(); \
            if (elect()) \
                asm volatile("cp.reduce.async.bulk.tensor.2d.global.shared::cta.add.tile.bulk_group [%0, {%2, %4}], [%1];\n" \
                             "cp.reduce.async.bulk.tensor.2d.global.shared::cta.add.tile.bulk_group [%0, {%3, %4}], [%1+16384];\n" \
                             "cp.async.bulk.commit_group;" ::"l"(&tmO), "r"(sm + (so) * SLOT + warp * 2048), "r"(128 * (ck)), "r"(128 * (ck) + 64), \
                             "r"(128 * (b >> 3) + 16 * warp) : "memory"); } while (0)
        if (fs) {
            mwait(BAR(B_FO));
            G4HALF(gg ^ 1, 4, 0); G4HALF(gg ^ 1, 4, 1); G4RED(gg ^ 1, 4);
            if (wq == 0) TS(74);
            mwait(BAR(B_FB));
        }
        if (warp == 0) TS(72);
        G4PAIR(8, Ho, 0, 1);
        if (!fs) G4HALF(gg ^ 1, 4, 0);
        G4PAIR(10, Hp, 0, 0);
        if (!fs) { G4HALF(gg ^ 1, 4, 1); if (lane == 0) marrive(BAR(B_FO)); }
        G4PAIR(12, Ho, 8, 0);
        if (!fs) { G4RED(gg ^ 1, 4); if (wq == 0) TS(73); }
        G4PAIR(14, Hp, 8, 0);
        mwait(BAR(B_SA));
#pragma unroll
        for (int q = 0; q < 8; q++) {
            const uint2 gv = lds64(sm + O_GB + (gg & 1) * 256 + c * 8 + q * 32);
            po[4 * q] = hmul2(gv.x, rp0); po[4 * q + 1] = hmul2(gv.x, rp1); po[4 * q + 2] = hmul2(gv.y, rp0); po[4 * q + 3] = hmul2(gv.y, rp1);
        }
        SCHED_FENCE();
        WG_WAIT(1);
        if (!fs && lane == 0) marrive(BAR(B_FB));
        WG_WAIT(0); pin(acc);
        if (wq == 0) TS(45 + fs);
#pragma unroll
        for (int q = 0; q < 8; q++)
            stsm4(SWZ(q & 3) + (8 + (q >> 2)) * SLOT, hmul2(po[4 * q], pk(acc[8 * q], acc[8 * q + 1])), hmul2(po[4 * q + 1], pk(acc[8 * q + 2], acc[8 * q + 3])),
                  hmul2(po[4 * q + 2], pk(acc[8 * q + 4], acc[8 * q + 5])), hmul2(po[4 * q + 3], pk(acc[8 * q + 6], acc[8 * q + 7])));
        G4RED(gg, 8);
        if (wq == 0) TS(47 + wg);
        asm volatile("cp.async.bulk.wait_group.read 0;" ::: "memory");
        if (fs && wq == 0) TS(51);
        WARRIVE(B_DONE);
    } else {
        unsigned ep;
        {
            const int rg = ba >> 4, cg = ba & 15;
            if (elect()) {
                const int cnt = wq < 2 ? 1 : 8;
#pragma unroll
                for (int i = 0; i < 32; i++) asm volatile("mbarrier.init.shared::cta.b64 [%0], %1;" ::"r"(BAR(32 * wq) + 8 * i), "r"((i >= 8 && wq == 3) ? 4 : cnt) : "memory");
                asm volatile("fence.mbarrier_init.release.cluster;" ::: "memory");
            }
            __syncwarp();
            if (wq < 2) {
                const int i = t128;
                const int tx = i < B_W2 ? 16384 : i < B_LH1 ? ((i >= B_W4 && (i & 2)) ? 24576 : 32768) : i < B_W1 ? 12288 : i < B_J ? 65536 : i == B_J ? (ba < 96 ? 32768 : 24576) : 8192;
                asm volatile("mbarrier.arrive.expect_tx.shared::cta.b64 _, [%0], %1;" ::"r"(BAR(i)), "r"(tx) : "memory");
            }
            __syncwarp();
            if (elect()) {
                if (wq == 1) tma2d(sm + O_T0, &tmM, 64 * cg, 64 * rg, BAR(B_J0));
                else if (wq == 3) asm volatile("prefetch.tensormap [%0];" ::"l"(&tmX) : "memory");
            }
            const unsigned short cr = ldg16(P.c + (64 * rg + (t128 & 63)));
            ep = ld_rlx(P.s->epoch + (ba * 32 + lane));
            asm volatile("barrier.cluster.arrive.relaxed.aligned;" ::: "memory");
            if (wq == 0) TS(77);
            if ((sm & 0xffffffu) != SM_BASE) __trap();
            unsigned* const dm = P.s->modp + (rg * 3072 + 64 * cg + 16 * wq + g + 8 * (c & 1));
            unsigned* const dc = P.s->csum + ((ba & 7) * 1792 + 64 * (ba >> 3) + 16 * wq + g + 8 * (c & 1));
            unsigned* const df = P.s->modf + ((wq - 1) * 512 + 4 * ba + (lane >> 3));
            if (c < 2) {
                st_rlx(dm, 0); st_rlx(dm + 1024, 0); st_rlx(dm + 2048, 0); st_rlx(dc, 0);
                if (ba < 96) st_rlx(dc + 1024, 0);
            }
            if (wq && (lane & 7) == 0) st_rlx(df, 0);
            if (wq < 2) stg128(P.s->hl + ((tau * 4 + gg) * 64 + t128), make_uint4(0, 0, 0, 0));
            const CUtensorMap* jm = &tmM + (lane >= 2);
            const int jc0 = lane < 2 ? 1024 * (lane + 1) + 64 * cg : 64 * (ba >> 3) + 1024 * (lane - 2), jc1 = 64 * (lane < 2 ? rg : ba & 7);
            const bool jon = wq == 3 && lane < (ba < 96 ? 4 : 3);
            SCHED_FENCE();
            asm volatile("barrier.cluster.wait.aligned;" ::: "memory");
            asm volatile("add.u32 %0, %0, 1;" : "+r"(ep));
            const unsigned tag = (ep & 0x7fu) | 0x80u;
            {
                const float v = b2f(cr);
                const bf16 o = __float2bfloat16_rn(wq < 2 ? __fdividef(v, 1.f + __expf(-v)) : 1.f);
                *(bf16*)(smem_raw + O_SV + t128 * 2) = o; *(bf16*)(smem_raw + O_SV + 256 + ((t128 * 2) ^ 32)) = o;
                FENCE_ASYNC_S();
                nbar(4, 128);
            }
#define JOB_MMA(d, off) _Pragma("unroll") for (int k = 0; k < 4; k++) wgmma_n8(d, mkdesc(0, (off) + k * 2048, 16), mkdesc(0, O_SV + k * 32, 16), k)
#define JOB_OUT(dst, d, col) red_xor(dst, ((__float_as_uint(c ? d[2 + (col)] : d[col]) + 0x80u) & 0xffffff00u) | tag)
            {
                mwaitb(BAR(B_J0));
                float d[4];
                WG_FENCE(); JOB_MMA(d, O_T0); WG_COMMIT();
                if (jon) asm volatile("cp.async.bulk.prefetch.tensor.2d.L2.global [%0, {%1,%2}];" ::"l"(jm), "r"(jc0), "r"(jc1) : "memory");
                __syncwarp();
                if (elect()) l2_prefetch(P.w1 + (ba * 2048 + wq * 512), 1024);
                WG_WAIT(0); pin(d);
                if (c < 2) JOB_OUT(dm, d, 0);
                if (wq == 0) TS(78);
            }
            if (wq >= 2) {
                mwaitb(BAR(B_XL + wq - 2));
                if (wq == 3) TS(81);
                const uint32_t a = sm + O_XG + (wq - 2) * 16384 + p * 8192;
                if (elect()) asm volatile("cp.async.bulk.shared::cluster.shared::cta.mbarrier::complete_tx::bytes [%0], [%1], 8192, [%2];"
                                          ::"r"(mapa(a, p ^ 1)), "r"(a), "r"(mapa(BAR(B_XG + wq - 2), p ^ 1)) : "memory");
            }
#pragma unroll 1
            for (int j = 0; j < 2; j++) {
                if (j || wq < 2) {
                    const int sg = 2 * j + wq, cn = 4 * ba + (lane >> 3);
                    float v = __uint_as_float(pollb(P.s->modp + ((lane & 7) * 3072 + sg * 512 + cn), tag, 0xffu) & 0xffffff00u);
                    v += __shfl_xor_sync(~0u, v, 1); v += __shfl_xor_sync(~0u, v, 2); v += __shfl_xor_sync(~0u, v, 4);
                    uint32_t o = pk(rbf(v) + ((sg == 1 || sg == 4) ? 1.f : 0.f), 0.f);
                    if (sg == 4 && o == 0) o = 0x3080;
                    if (sg != 3 && sg != 5) *(unsigned short*)(smem_raw + O_ML + (sg == 4 ? 3 : sg) * 8 + (lane >> 3) * 2) = (unsigned short)o;
                    if (sg >= 3 && (lane & 7) == 0) red_xor(df, (o << 16) | tag);
                    if (wq == 0) TS(54 + j);
                }
                WARRIVE(B_MOD0 + j);
                if (j) break;
                mwaitb(BAR(B_KP));
                {
                    const uint32_t k0 = sm + wq * KST_W + (lane & 15) * (2 * KP_P), ft = sm + O_FT + wq * FT_CH + 64 + lane * 8;
                    const uint32_t a2 = k0 + (12 + 2 * (lane >> 4)) * 4, a3 = k0 + (16 + (lane >> 4)) * 4, nx = (lane & 15) == 15 ? 4 - 30 * KP_P : 2 * KP_P;
#pragma unroll 1
                    for (int h = 0; h < 2; h++) {
                        const uint32_t o[4] = {h ? a3 + nx : a2 + 4, h ? a3 + nx + 8 : a2 + KP_P, h ? a3 + KP_P : a2 + KP_P + 4, h ? a3 + KP_P + 8 : a2 + nx + ((lane & 15) == 15 ? 4 : 0)};
                        float v[4];
#pragma unroll
                        for (int it = 0; it < 4; it++) v[it] = ldsf(o[it]) + ldsf(o[it] + 4 * KST_W);
#pragma unroll
                        for (int it = 0; it < 4; it++) {
                            const bool cont = h && (it & 1);
                            const float pv = __shfl_sync(~0u, lane == 31 ? (cont ? v[it & 2] : 0.f) : v[it], lane - 1);
                            const uint32_t d = ft + (h ? 1792 + (it >> 1) * 576 + (it & 1) * 256 : it * 448), t = pk(v[it], pv);
                            sts32(d, t);
                            if (!cont || lane < 24) sts32(d + 68, t);
                            if (!h && lane == 31) {
                                const uint32_t u = t << 16;
                                sts32(d + 8, u); sts32(d + 76, u);
                                if (it == 3) { const uint32_t e = ft + 2944 - 248; sts32(e, t & 0xffffu); sts32(e + 68, t & 0xffffu); sts32(e + 8, u); sts32(e + 76, u); }
                            }
                        }
                    }
                }
                if (wq == 0) TS(56);
                mwaitb(BAR(B_TAB));
                if (jon) tma2d(sm + O_T1 + lane * T_STRIDE, jm, jc0, jc1, BAR(B_J));
                __syncwarp();
                if (elect()) { l2_prefetch(P.w2 + (ba * 2048 + wq * 512), 1024); l2_prefetch(P.w4 + (ba * 7168 + wq * 1792), 3584); }
                {
                    mwaitb(BAR(B_XD));
                    if (wq == 0) TS(57);
                    const uint32_t ub = sm + O_U + wq * U_CH + 112 + (lane >> 1) * 16, bo = sm + O_BOX + wq * BOX_CH;
                    const int hf = lane & 1;
                    if (lane < 3) sts128(bo + (lane == 2 ? B9_O + H3O : lane * 3200 + H2O), 0, 0, 0, 0);
#pragma unroll 1
                    for (int it = 0; it < 6; it++) {
                        const uint2 u0 = lds64(ub + it * 256 + hf * U_H + 8);
                        const uint4 u1 = lds128(ub + it * 256 + (hf ? 16 : U_H)), u2 = lds128(ub + it * 256 + hf * U_H + 16);
                        const uint32_t E[9] = {u0.x, u0.y, u1.x, u1.y, u1.z, u1.w, u2.x, u2.y, u2.z};
                        uint32_t O[8], A[8], F[6];
#pragma unroll
                        for (int k = 0; k < 8; k++) { O[k] = __byte_perm(E[k], E[k + 1], 0x5432); A[k] = hadd2(E[k], O[k]); }
#pragma unroll
                        for (int k = 0; k < 6; k++) F[k] = hadd2(A[k], A[k + 1]);
                        const uint32_t o2 = bo + hf * H2O + (16 * it + (lane >> 1) + 1) * 16, o3 = o2 - hf * (H2O - H3O);
                        sts128(o2 + B5_O, hadd2(F[1], E[3]), hadd2(F[2], E[4]), hadd2(F[3], E[5]), hadd2(F[4], E[6]));
                        sts128(o2 + B3_O, hadd2(O[3], A[4]), hadd2(O[4], A[5]), hadd2(O[5], A[6]), hadd2(O[6], A[7]));
                        if (it < 4) {
                            sts128(o3 + B9_O, hadd2(F[0], hadd2(F[2], E[4])), hadd2(F[1], hadd2(F[3], E[5])), hadd2(F[2], hadd2(F[4], E[6])), hadd2(F[3], hadd2(F[5], E[7])));
                            sts128(o3 + B7_O, hadd2(hadd2(O[0], A[1]), F[2]), hadd2(hadd2(O[1], A[2]), F[3]), hadd2(hadd2(O[2], A[3]), F[4]), hadd2(hadd2(O[3], A[4]), F[5]));
                            sts128(o3 + B2_O, A[4], A[5], A[6], A[7]);
                        }
                        if (it == 1) {
                        WARRIVE(B_FAR);
                {
                    mwaitb(BAR(B_J));
                    if (wq == 0) TS(79);
                    float d[4][4];
                    WG_FENCE();
#pragma unroll
                    for (int i = 0; i < 4; i++) { JOB_MMA(d[i], O_T1 + i * T_STRIDE); }
                    WG_COMMIT();
                    WG_WAIT(0);
#pragma unroll
                    for (int i = 0; i < 4; i++) pin(d[i]);
                    nbar(4, 128);
                    if (elect()) {
                        tma2d(sm + wq * SLOT, &tmW1, 128 * gg, 128 * wq, BAR(B_W1));
                        if (wq < 3) tma2d(sm + (4 + wq) * SLOT, &tmW1, 128 * gg + 64, 128 * wq, BAR(B_W1 + 1));
                        asm volatile("prefetch.tensormap [%0];" ::"l"(wq ? &tmW1 + wq : &tmO) : "memory"); asm volatile("prefetch.tensormap [%0];" ::"l"(&tmW4 + wq) : "memory");
                    }
                    if (c < 2) {
                        JOB_OUT(dm + 1024, d[0], 0); JOB_OUT(dm + 2048, d[1], 0); JOB_OUT(dc, d[2], 1);
                        if (ba < 96) JOB_OUT(dc + 1024, d[3], 1);
                    }
                    if (wq == 0) TS(80);
                }
                        }
                    }
                    WARRIVE(B_FAR + 1);
                    if (wq == 0) TS(58);
                }
            }
            if (wq == 0) TS(60);
        }
        asm volatile("setmaxnreg.dec.sync.aligned.u32 40;");
        if (wq >= 2) {
            mwaitb(BAR(B_CEND));
            if (wq == 3) { if (elect()) tma2d(sm + 7 * SLOT, &tmW1, 128 * gg + 64, 384, BAR(B_W1 + 1)); }
            else {
                if (elect()) publish(P.s->f0);
                TS(19);
                pollb(P.s->f0, 128 * ep, ~0u);
                TS(21);
                FENCE_ASYNC_G();
#pragma unroll
                for (int q = 0; q < 4; q++) {
                    if (q >= 2) mwait(BAR(B_HF + 4 * p + q - 2));
                    if (elect()) tma2d_mc(sm + O_A + (4 * p + q) * 8192, &tmXS, 64 * tau, 64 * (4 * p + q), BAR(B_HF + 4 * p + q));
                }
            }
        }
        else {
            mwait(BAR(B_BT));
            float4 gs = ldsf4(sm + O_GC + c * 16); float g4 = ldsf(sm + O_GC + 64 + c * 4);
            gs.x = qsum(gs.x); gs.y = qsum(gs.y); gs.z = qsum(gs.z); gs.w = qsum(gs.w); g4 = qsum(g4);
            SCHED_FENCE();
            const uint32_t a = sm + O_RP + t128 * 32;
            mwait(BAR(B_RP));
            const float4 t = ldsf4(a), u = ldsf4(a + 2048);
            const float2 t2 = ldsf2(a + 16), u2 = ldsf2(a + 2064);
            float m1, r1, m2, r2;
            row_stats(t.x + u.x, t2.x + u2.x, m1, r1);
            row_stats(fmaf(r1, fmaf(-m1, gs.x, t.y + u.y), gs.y),
                      fmaf(r1, fmaf(r1, fmaf(m1, fmaf(m1, gs.z, -2.f * (t.z + u.z)), t2.y + u2.y), 2.f * fmaf(-m1, gs.w, t.w + u.w)), g4), m2, r2);
            r2 *= GK0;
            const uint32_t pz = pk(-r2 * m2, r1);
            sts128(sm + O_RC + t128 * 16, __float_as_uint(r1 * r2), pk(-r1 * r2 * m1, r2), pz, pk(-m1 * bhi(pz), 0.f));
            WARRIVE_N(B_RC, 2);
            if (wq == 0) TS(24);
#pragma unroll 1
            for (int h = 0; h < 2; h++) {
            const int i = min(t128 + 64 * h, 111);
            const unsigned* s = P.s->csum + (224 * fj + 2 * i);
            unsigned t[8][2], bad;
            do {
                bad = 0;
#pragma unroll
                for (int r = 0; r < 8; r++) asm volatile("ld.relaxed.gpu.global.v2.u32 {%0,%1}, [%2];" : "=r"(t[r][0]), "=r"(t[r][1]) : "l"(s + r * 1792) : "memory");
#pragma unroll
                for (int r = 0; r < 8; r++) bad |= (t[r][0] ^ (ep | 0x80u)) | (t[r][1] ^ (ep | 0x80u));
            } while (__any_sync(~0u, bad & 0xffu));
            float a0 = 0.f, a1 = 0.f;
#pragma unroll
            for (int r = 0; r < 8; r++) { a0 += __uint_as_float(t[r][0] & 0xffffff00u); a1 += __uint_as_float(t[r][1] & 0xffffff00u); }
            sts32(sm + O_V4 + (i >> 3) * 32 + (i & 3) * 8 + (i & 4), pk(a0, a1));
        }
        if (wq == 0) TS(76);
            WARRIVE_N(B_V4, 2);
            {
                const int tn = tau + ((gg & 1) ? 1 : -1);
                uint32_t d[8] = {0, 0, 0, 0, 0, 0, 0, 0};
                mwait(BAR(B_PH));
                if ((unsigned)tn < 32u) {
                    const uint4* hp = P.s->hl + ((tn * 4 + (gg ^ (2 * wq))) * 64 + 2 * lane);
                    do {
                        asm volatile("{\n.reg .b64 a, b, c, d;\nld.relaxed.gpu.global.v2.b64 {a, b}, [%8];\nld.relaxed.gpu.global.v2.b64 {c, d}, [%8+16];\n"
                                     "mov.b64 {%0, %1}, a;\nmov.b64 {%2, %3}, b;\nmov.b64 {%4, %5}, c;\nmov.b64 {%6, %7}, d;\n}"
                                     : "=r"(d[0]), "=r"(d[1]), "=r"(d[2]), "=r"(d[3]), "=r"(d[4]), "=r"(d[5]), "=r"(d[6]), "=r"(d[7]) : "l"(hp) : "memory");
                    } while (__any_sync(~0u, ((d[1] ^ ep) | (d[3] ^ ep) | (d[5] ^ ep) | (d[7] ^ ep)) != 0));
                }
                sts128(sm + O_HB + t128 * 16, d[0], d[2], d[4], d[6]);
                WARRIVE_N(B_HB, 2);
            }
        }
        if (wq == 0) {
            mwait(BAR(B_V4)); mwait(BAR(B_HD)); mwait<1>(BAR(B_HF + 6 + p));
#pragma unroll 1
            for (int i = 0; i < 16; i++) {
                mwait(BAR(B_E2 + ((0xDDCBA98765410000ull >> (4 * i)) & 15)));
                if (elect()) tma3d(sm + W3A(i), &tmW3 + (i >> 3), 224 * fj + (i >> 3) * 128, 128 * ZG((i >> 1) & 3) + 64 * (i & 1), 0, BAR(B_W3 + i));
            }
            P.s->epoch[ba * 32 + lane] = ep;
        } else if (wq == 1) {
            if (lane < 4) asm volatile("mbarrier.arrive.expect_tx.shared::cta.b64 _, [%0], 8192;" ::"r"(BAR(B_HF + 4 + lane)) : "memory");
            poll(P.s->fh + min(max(tau + ((lane & 1) ? 0 : (gg & 1) ? -1 : 1), 0), 31) * 32, 4 * ep);
            TS(84);
            if (elect()) {
                FENCE_ASYNC_G();
#pragma unroll
                for (int q = 2; q < 4; q++)
                    tma2d_mc(sm + O_A + q * SLOT + p * 8192, &tmH, 128 * ZG(q) + 64 * p, 64 * tau + ((gg & 1) ? 3 - q : 1 + q), BAR(B_HF + 2 * q + p));
            }
            mwait(BAR(B_ZL)); mwait(BAR(B_PZP));
            if (elect()) {
                const uint32_t a = sm + (2 * p + hh) * SLOT;
                asm volatile("cp.async.bulk.shared::cluster.shared::cta.mbarrier::complete_tx::bytes [%0], [%1], 16384, [%2];"
                             ::"r"(mapa(a, p ^ 1)), "r"(a), "r"(mapa(BAR(B_ZF + 2 * p + hh), p ^ 1)) : "memory");
            }
            poll(P.s->fz + (b >> 3) * 32, 8 * ep);
            TS(86);
            FENCE_ASYNC_G();
#pragma unroll
            for (int i = 0; i < 6; i++) {
                const int u = i < 2 ? i : 1 + (i >> 1), w = hh ^ (i < 2 ? 1 : i & 1);
                if (i == 2 || i == 4) mwait(BAR(B_ZF + (i == 2 ? hh ^ 1 : 4 + hh)));
                if (elect()) bulk_ld_mc(sm + (2 * u + w) * SLOT + p * 8192, P.s->z + (((tau & ~1) + w) * 8 + 2 * ZG(u) + p) * 512, 8192, BAR(B_ZF + 2 * u + w));
            }
#pragma unroll 1
            for (int j = 0; j < 8; j++) {
                const int k0 = 224 * (fj ^ (j & 1)) + 64 * (j & 2), pn = 2 * (gg ^ 1 ^ (j >> 2)), sl = (int)(W4SLOT >> (8 * j));
                mwait(BAR(B_ST + 10 + ((0x76655420 >> (4 * j)) & 15)));
                if (elect()) tma3d(sm + (sl & 15) * SLOT, &tmW4, 0, k0, pn, BAR(B_W4 + j));
                if (j < 2) mwait(BAR(B_ST + 11 + 2 * j));
                if (elect()) tma3d(sm + ((sl >> 4) & 15) * SLOT, &tmW4 + ((j >> 1) & 1), 0, k0 + 64, pn, BAR(B_W4 + j));
            }
        } else {
            if (wq == 2) {
#pragma unroll 1
                for (int i = 0; i < 8; i++) {
                    const int pn = i & 1, sl = (i >> 1) ^ (2 * pn);
                    mwait(BAR(B_E1 + i));
                    if (elect()) tma2d(sm + (4 * pn + sl) * SLOT, &tmW2, 128 * gg + 64 * pn, 128 * (i < 4 ? gg ^ (i & 2) : ZG(i >> 1)), BAR(B_W2 + (i >> 1)));
                }
                mwait(BAR(B_PH));
                if (elect()) asm volatile("mbarrier.arrive.shared::cluster.b64 _, [%0], 4;" ::"r"(mapa(BAR(B_PHP), p ^ 1)) : "memory");
                mwait(BAR(B_PHP));
                if (elect()) asm volatile("cp.async.bulk.shared::cluster.shared::cta.mbarrier::complete_tx::bytes [%0], [%1], 16384, [%2];"
                                          ::"r"(mapa(sm + O_A, p ^ 1)), "r"(sm + 12 * SLOT), "r"(mapa(BAR(B_HP), p ^ 1)) : "memory");
            }
            mwaitb(BAR(B_PH + 3 - wq));
            if (elect()) publish(wq == 3 ? P.s->fh + tau * 32 : P.s->fz + (b >> 3) * 32);
            TS(88 + wq - 2);
            if (wq == 2) {
                mwait(BAR(B_BA)); mwait(BAR(B_ZF + 4 + (hh ^ 1)));
                unsigned* fb = P.s->fb + (2 * (b >> 3) + p) * 32;
                if (elect()) {
#pragma unroll 1
                    for (int i = 0; i < 8; i++)
                        asm volatile("cp.async.bulk.tensor.2d.global.shared::cta.tile.bulk_group [%0, {%2, %3}], [%1];"
                                     ::"l"(&tmO), "r"(sm + 11 * SLOT + i * 2048), "r"(128 * gg + 64 * (i >> 2)), "r"(64 * tau + 16 * (i & 3)) : "memory");
                    asm volatile("cp.async.bulk.commit_group;\ncp.async.bulk.wait_group.read 0;" ::: "memory");
                    asm volatile("mbarrier.arrive.shared::cluster.b64 _, [%0], 4;" ::"r"(mapa(BAR(B_CRA), p ^ 1)) : "memory");
                    asm volatile("cp.async.bulk.wait_group 0;" ::: "memory");
                    FENCE_ASYNC_G();
                    publish(fb);
                }
                TS(90);
                poll(fb, 4 * ep);
                WARRIVE_N(B_BS, 4);
                TS(91);
            } else {
                mwaitb(BAR(B_DONE));
            }
        }
    }
}

typedef CUresult (*EncodeFn)(CUtensorMap*, CUtensorMapDataType, cuuint32_t, void*, const cuuint64_t*, const cuuint64_t*, const cuuint32_t*,
                             const cuuint32_t*, CUtensorMapInterleave, CUtensorMapSwizzle, CUtensorMapL2promotion, CUtensorMapFloatOOBfill);

static void make_map(EncodeFn enc, CUtensorMap* m, const void* base, int rank, const cuuint64_t* dims, const cuuint64_t* strides,
                     const cuuint32_t* box, CUtensorMapSwizzle sw) {
    cuuint32_t es[3] = {1, 1, 1};
    enc(m, CU_TENSOR_MAP_DATA_TYPE_BFLOAT16, rank, (void*)base, dims, strides, box, es, CU_TENSOR_MAP_INTERLEAVE_NONE, sw,
        CU_TENSOR_MAP_L2_PROMOTION_L2_128B, CU_TENSOR_MAP_FLOAT_OOB_FILL_NONE);
}

extern "C" void kernel_launch(void* const* d_in, const int* in_sizes, int n_in, void* d_out, int out_size) {
    Params P;
    P.x = (const bf16*)d_in[0];
    for (int i = 0; i < 8; i++) P.par[i] = (const bf16*)d_in[1 + i];
    P.w1 = (const bf16*)d_in[10]; P.w2 = (const bf16*)d_in[11]; P.w3 = (const bf16*)d_in[12];
    P.w4 = (const bf16*)d_in[13]; P.c = (const bf16*)d_in[14]; P.wmod = (const bf16*)d_in[15]; P.out = (bf16*)d_out;

    void* fn = nullptr; cudaDriverEntryPointQueryResult qr;
    cudaGetDriverEntryPoint("cuTensorMapEncodeTiled", &fn, cudaEnableDefault, &qr);
    EncodeFn enc = (EncodeFn)fn;
    void* hbuf = nullptr; cudaGetSymbolAddress(&hbuf, g_s);
    P.s = (Scratch*)hbuf;
    Maps M;
    { cuuint64_t d[3] = {512, 256, 8}, s[2] = {8192, 1024}; cuuint32_t bx[3] = {8, 128, 4}; make_map(enc, &tmX, P.x, 3, d, s, bx, CU_TENSOR_MAP_SWIZZLE_NONE); }
    { cuuint64_t d[2] = {512, 512}, s[1] = {1024}; cuuint32_t bx[2] = {64, 128};
      make_map(enc, &tmW1, P.w1, 2, d, s, bx, CU_TENSOR_MAP_SWIZZLE_128B); make_map(enc, &tmW2, P.w2, 2, d, s, bx, CU_TENSOR_MAP_SWIZZLE_128B); }
    { cuuint64_t d[3] = {1792, 512, 2}, s[2] = {3584, 128}, sb[2] = {3584, 64}; cuuint32_t bx[3] = {64, 64, 2};
      make_map(enc, &tmW3, P.w3, 3, d, s, bx, CU_TENSOR_MAP_SWIZZLE_128B); make_map(enc, &tmW3b, P.w3, 3, d, sb, bx, CU_TENSOR_MAP_SWIZZLE_128B); }
    { cuuint64_t d[3] = {64, 1792, 8}, s[2] = {1024, 128}; cuuint32_t bx[3] = {64, 64, 2}, bh[3] = {64, 32, 2};
      make_map(enc, &tmW4, P.w4, 3, d, s, bx, CU_TENSOR_MAP_SWIZZLE_128B); make_map(enc, &tmW4h, P.w4, 3, d, s, bh, CU_TENSOR_MAP_SWIZZLE_128B); }
    for (int i = 0; i < 4; i++) {
        cuuint64_t w = i == 0 ? 512 : i == 1 ? 2048 : i == 2 ? 3072 : 1792, d[2] = {w, i == 0 ? 2052u : 512u}, s[1] = {2 * w}; cuuint32_t bx[2] = {64, 64};
        make_map(enc, &tmH + i, i == 0 ? P.s->h : i == 1 ? P.s->xs : i == 2 ? P.wmod : P.w3, 2, d, s, bx, CU_TENSOR_MAP_SWIZZLE_128B);
    }
    { cuuint64_t d[2] = {512, 2048}, s[1] = {1024}; cuuint32_t bx[2] = {64, 16}; make_map(enc, &tmO, P.out, 2, d, s, bx, CU_TENSOR_MAP_SWIZZLE_128B); }
    cudaFuncSetAttribute(fused_kernel, cudaFuncAttributeMaxDynamicSharedMemorySize, SMEM_BYTES);
    fused_kernel<<<128, 384, SMEM_BYTES, cudaStreamPerThread>>>(P, M);
}
```

```cpp
#include <cuda_runtime.h>
#include <cuda_bf16.h>
#include <cuda.h>
#include <stdint.h>
#include <stddef.h>

typedef __nv_bfloat16 bf16;
typedef unsigned long long u64;

struct Scratch {
    bf16     h[2052 * 512];
    uint4    z[32 * 8 * 512];
    bf16     xs[512 * 2048];
    uint4    hl[32 * 4 * 64];
    float2   zst[32 * 8 * 64];
    unsigned stats[2048];
    unsigned modp[8 * 3072];
    unsigned csum[8 * 1792];
    unsigned modf[3 * 512];
    unsigned f0[32], fh[32 * 32], fz[16 * 32], fb[32 * 32], epoch[128 * 32];
};
__device__ __align__(1024) Scratch g_s;
#define TS(i)

struct Params {
    const bf16* par[8];
    const bf16 *x, *wmod, *c;
    Scratch* s;
    const bf16 *w1, *w2, *w3, *w4;
    bf16* out;
};
struct Maps { CUtensorMap m[12]; };
#define tmX M.m[0]
#define tmW1 M.m[1]
#define tmW2 M.m[2]
#define tmW3 M.m[3]
#define tmW3b M.m[4]
#define tmW4 M.m[5]
#define tmW4h M.m[6]
#define tmH M.m[7]
#define tmXS M.m[8]
#define tmO M.m[11]
#define tmM M.m[9]

constexpr uint32_t SLOT = 16384;
constexpr uint32_t KST_P = 272, KST_W = 53 * 272, KP_P = 112;
constexpr uint32_t FT_CH = 3520, O_FT = 8 * SLOT - 4 * FT_CH;
constexpr uint32_t O_BOX = 8 * SLOT, BOX_CH = 12928, B5_O = 0, B3_O = 3200, B9_O = 6400, B7_O = 8576, B2_O = 10752;
constexpr uint32_t H2O = 1600, H3O = 1088;
constexpr uint32_t O_XG = O_BOX;
constexpr uint32_t O_U = O_BOX + 4 * BOX_CH, U_CH = 4480, U_H = 2240;
constexpr uint32_t O_NT = O_U + 4 * U_CH, NT_CH = 4496, NT_R = 280, NT_B = 2252;
constexpr uint32_t O_Y0 = O_NT + 4 * NT_CH, Y_CH = 2112;
constexpr uint32_t O_SV = (O_Y0 + 4 * Y_CH + 1023) / 1024 * 1024;
constexpr uint32_t O_T0 = (O_U + 1023) / 1024 * 1024, O_T1 = 4096, T_STRIDE = 14336;
constexpr uint32_t O_PAR = O_Y0, O_XR = O_XG + 32768;
constexpr uint32_t O_A = 8 * SLOT;
constexpr uint32_t O_BT = 13 * SLOT, O_VT = O_BT + 8192, O_GC = O_VT + 768, O_RC = O_GC + 80, O_RP = O_RC + 1024, O_HB = O_BT + 14336;
constexpr uint32_t O_BAR = 14 * SLOT, O_IC = O_BAR + 1056, O_GB = O_IC + 512, O_V4 = O_GB + 512, O_ML = O_V4 + 448;
static_assert(8 * KST_W <= O_FT && O_FT >= 7 * SLOT && 7 * KST_W + 32 * KP_P <= 7 * SLOT, "smem map");
constexpr u64 W3SLOT = 0x1A98DCA98DCA98DCull, W4SLOT = 0x320BDC761A9832DCull;
constexpr uint32_t SMEM_BYTES = 232448;
static_assert(O_SV + 1024 <= 14 * SLOT && O_ML + 68 <= SMEM_BYTES, "smem map");

enum {
    B_ZF = 0, B_W3 = 8, B_LH0 = 24, B_HP = 26,
    B_W2 = 30, B_W4 = 36,
    B_LH1 = 44,
    B_W1 = 46,
    B_J = 48,
    B_J0 = 49, B_HF = 50, B_XL = 58, B_XG = 62,
    B_KP = 64, B_TAB, B_CEND, B_DONE, B_PH, B_PZ, B_CR0, B_CR1, B_RP, B_E2 = 73, B_HS = 75, B_ZL = 76, B_ST = 77, B_T4 = 93, B_BA = 95, B_E1 = 96,
    B_U = 104, B_FAR = 106, B_MOD0 = 108, B_MOD1, B_BT, B_RC, B_V4, B_FB, B_FA, B_FO, B_SA, B_BS, B_CRA, B_XD, B_PZP, B_HB, B_PHP, B_HD,
    B_PAR = 128, B_XR
};

#define DI __device__ __forceinline__
#define SCHED_OPEN(v) uint32_t v; asm volatile("mov.u32 %0, %%clock;" : "=r"(v)::"memory")
#define SCHED_CLOSE(v) asm volatile("{\n.reg .u32 t;\nmov.u32 t, %%clock;\nst.shared.v2.u32 [%0], {t, %1};\n}" ::"r"(sm + O_ML + 64), "r"(v) : "memory")
#define SCHED_FENCE() asm volatile("{\n.reg .u32 t;\nmov.u32 t, %%clock;\nst.shared.u32 [%0], t;\n}" ::"r"(sm + O_ML + 64) : "memory")
template <int PH = 0> DI void mwait(uint32_t bar) {
    asm volatile("{\n.reg .pred p;\nWL: fence.mbarrier_init.release.cluster;\nmbarrier.try_wait.parity.shared::cta.b64 p, [%0], %1;\n@!p bra.uni WL;\n}" ::"r"(bar), "n"(PH) : "memory");
}
DI bool mtry(uint32_t bar) {
    uint32_t r; asm volatile("{\n.reg .pred p;\nmbarrier.test_wait.parity.shared::cta.b64 p, [%1], 0;\nselp.u32 %0, 1, 0, p;\n}" : "=r"(r) : "r"(bar) : "memory"); return r;
}
DI void mwaitb(uint32_t bar) {
    asm volatile("{\n.reg .pred p;\n.reg .u32 n;\nmov.u32 n, 0;\n"
                 "WL: mbarrier.try_wait.parity.shared::cta.b64 p, [%0], 0;\n@p bra.uni WD;\n"
                 "add.u32 n, n, 1;\nsetp.lt.u32 p, n, 2000000;\n@p bra.uni WL;\ntrap;\nWD:\n}" ::"r"(bar) : "memory");
}
DI bool elect() { uint32_t r; asm volatile("{\n.reg .pred p;\nelect.sync _|p, 0xffffffff;\nselp.u32 %0, 1, 0, p;\n}" : "=r"(r)); return r; }
DI void marrive_n(uint32_t bar, int n) { asm volatile("mbarrier.arrive.shared::cta.b64 _, [%0], %1;" ::"r"(bar), "r"(n) : "memory"); }
DI void marrive(uint32_t bar) { asm volatile("mbarrier.arrive.shared::cta.b64 _, [%0];" ::"r"(bar) : "memory"); }
DI void marrive_rem(uint32_t bar) { asm volatile("mbarrier.arrive.shared::cluster.b64 _, [%0];" ::"r"(bar) : "memory"); }
DI uint32_t mapa(uint32_t a, uint32_t r) { uint32_t o; asm("mapa.shared::cluster.u32 %0, %1, %2;" : "=r"(o) : "r"(a), "r"(r)); return o; }
DI void nbar(int id, int n) { asm volatile("bar.sync %0, %1;" ::"r"(id), "r"(n) : "memory"); }
DI uint32_t lds32(uint32_t a) { uint32_t v; asm volatile("ld.shared.u32 %0, [%1];" : "=r"(v) : "r"(a)); return v; }
DI uint32_t lds32v(uint32_t a) { uint32_t v; asm volatile("ld.volatile.shared.u32 %0, [%1];" : "=r"(v) : "r"(a)); return v; }
DI float ldsf(uint32_t a) { float v; asm volatile("ld.shared.f32 %0, [%1];" : "=f"(v) : "r"(a)); return v; }
DI uint2 lds64(uint32_t a) { uint2 v; asm volatile("ld.shared.v2.u32 {%0,%1}, [%2];" : "=r"(v.x), "=r"(v.y) : "r"(a)); return v; }
DI float2 ldsf2(uint32_t a) { float2 v; asm volatile("ld.shared.v2.f32 {%0,%1}, [%2];" : "=f"(v.x), "=f"(v.y) : "r"(a)); return v; }
DI uint4 lds128(uint32_t a) { uint4 v; asm volatile("ld.shared.v4.u32 {%0,%1,%2,%3}, [%4];" : "=r"(v.x), "=r"(v.y), "=r"(v.z), "=r"(v.w) : "r"(a)); return v; }
DI float4 ldsf4(uint32_t a) { float4 v; asm volatile("ld.shared.v4.f32 {%0,%1,%2,%3}, [%4];" : "=f"(v.x), "=f"(v.y), "=f"(v.z), "=f"(v.w) : "r"(a)); return v; }
DI void sts32(uint32_t a, uint32_t v) { asm volatile("st.shared.u32 [%0], %1;" ::"r"(a), "r"(v) : "memory"); }
DI void stsf(uint32_t a, float v) { asm volatile("st.shared.f32 [%0], %1;" ::"r"(a), "f"(v) : "memory"); }
DI void sts64(uint32_t a, uint32_t x, uint32_t y) { asm volatile("st.shared.v2.u32 [%0], {%1,%2};" ::"r"(a), "r"(x), "r"(y) : "memory"); }
DI void stsf2(uint32_t a, float x, float y) { asm volatile("st.shared.v2.f32 [%0], {%1,%2};" ::"r"(a), "f"(x), "f"(y) : "memory"); }
DI void sts128(uint32_t a, uint32_t x, uint32_t y, uint32_t z, uint32_t w) { asm volatile("st.shared.v4.u32 [%0], {%1,%2,%3,%4};" ::"r"(a), "r"(x), "r"(y), "r"(z), "r"(w) : "memory"); }
DI void stsf4(uint32_t a, float x, float y, float z, float w) { asm volatile("st.shared.v4.f32 [%0], {%1,%2,%3,%4};" ::"r"(a), "f"(x), "f"(y), "f"(z), "f"(w) : "memory"); }
DI void ldsm4(uint32_t a, uint32_t& r0, uint32_t& r1, uint32_t& r2, uint32_t& r3) {
    asm volatile("ldmatrix.sync.aligned.m8n8.x4.shared.b16 {%0,%1,%2,%3}, [%4];" : "=r"(r0), "=r"(r1), "=r"(r2), "=r"(r3) : "r"(a));
}
DI void ldsm4t(uint32_t a, uint32_t& r0, uint32_t& r1, uint32_t& r2, uint32_t& r3) {
    asm volatile("ldmatrix.sync.aligned.m8n8.x4.trans.shared.b16 {%0,%1,%2,%3}, [%4];" : "=r"(r0), "=r"(r1), "=r"(r2), "=r"(r3) : "r"(a));
}
DI void stsm4(uint32_t a, uint32_t r0, uint32_t r1, uint32_t r2, uint32_t r3) {
    asm volatile("stmatrix.sync.aligned.m8n8.x4.shared.b16 [%0], {%1,%2,%3,%4};" ::"r"(a), "r"(r0), "r"(r1), "r"(r2), "r"(r3) : "memory");
}
DI void stsm4t(uint32_t a, uint32_t r0, uint32_t r1, uint32_t r2, uint32_t r3) {
    asm volatile("stmatrix.sync.aligned.m8n8.x4.trans.shared.b16 [%0], {%1,%2,%3,%4};" ::"r"(a), "r"(r0), "r"(r1), "r"(r2), "r"(r3) : "memory");
}
DI void mma(float (&d)[4], uint32_t a0, uint32_t a1, uint32_t a2, uint32_t a3, uint32_t b0, uint32_t b1) {
    asm volatile("mma.sync.aligned.m16n8k16.row.col.f32.bf16.bf16.f32 {%0,%1,%2,%3}, {%4,%5,%6,%7}, {%8,%9}, {%0,%1,%2,%3};"
                 : "+f"(d[0]), "+f"(d[1]), "+f"(d[2]), "+f"(d[3]) : "r"(a0), "r"(a1), "r"(a2), "r"(a3), "r"(b0), "r"(b1));
}
DI uint32_t pk(float lo, float hi) { uint32_t r; asm("cvt.rn.bf16x2.f32 %0, %1, %2;" : "=r"(r) : "f"(hi), "f"(lo)); return r; }
DI float blo(uint32_t v) { return __uint_as_float(v << 16); }
DI float bhi(uint32_t v) { return __uint_as_float(v & 0xffff0000u); }
DI float rbf(float v) { return __bfloat162float(__float2bfloat16_rn(v)); }
DI uint4 ldg128(const void* p) { uint4 v; asm volatile("ld.global.nc.L1::no_allocate.v4.u32 {%0,%1,%2,%3}, [%4];" : "=r"(v.x), "=r"(v.y), "=r"(v.z), "=r"(v.w) : "l"(p)); return v; }
DI uint32_t ldg32(const void* p) { uint32_t v; asm volatile("ld.global.nc.u32 %0, [%1];" : "=r"(v) : "l"(p)); return v; }
DI unsigned short ldg16(const bf16* p) { unsigned short v; asm volatile("ld.global.nc.u16 %0, [%1];" : "=h"(v) : "l"(p)); return v; }
DI float b2f(unsigned short h) { float v; asm volatile("{\n.reg .b32 t;\ncvt.u32.u16 t, %1;\nshl.b32 %0, t, 16;\n}" : "=f"(v) : "h"(h)); return v; }
DI uint4 ldw128(const void* p) { uint4 v; asm volatile("ld.global.v4.u32 {%0,%1,%2,%3}, [%4];" : "=r"(v.x), "=r"(v.y), "=r"(v.z), "=r"(v.w) : "l"(p) : "memory"); return v; }
DI uint32_t ldw32(const void* p) { uint32_t v; asm volatile("ld.global.u32 %0, [%1];" : "=r"(v) : "l"(p) : "memory"); return v; }
DI float ldgbf(const bf16* p) { unsigned short v; asm volatile("ld.global.nc.u16 %0, [%1];" : "=h"(v) : "l"(p)); return __uint_as_float((uint32_t)v << 16); }
DI uint4 ldc128(const void* p) { uint4 v; asm volatile("ld.global.L1::no_allocate.v4.u32 {%0,%1,%2,%3}, [%4];" : "=r"(v.x), "=r"(v.y), "=r"(v.z), "=r"(v.w) : "l"(p) : "memory"); return v; }
DI uint2 ld_rlx64(const void* p) { uint2 v; asm volatile("{\n.reg .b64 t;\nld.relaxed.gpu.global.b64 t, [%2];\nmov.b64 {%0, %1}, t;\n}" : "=r"(v.x), "=r"(v.y) : "l"(p) : "memory"); return v; }
DI uint2 ldc64(const void* p) { uint2 v; asm volatile("ld.global.L1::no_allocate.v2.u32 {%0,%1}, [%2];" : "=r"(v.x), "=r"(v.y) : "l"(p) : "memory"); return v; }
DI uint32_t ldc32(const void* p) { uint32_t v; asm volatile("ld.global.L1::no_allocate.u32 %0, [%1];" : "=r"(v) : "l"(p) : "memory"); return v; }
DI void stg128(void* p, uint4 v) { asm volatile("st.global.v4.u32 [%0], {%1,%2,%3,%4};" ::"l"(p), "r"(v.x), "r"(v.y), "r"(v.z), "r"(v.w) : "memory"); }
DI void st_rlx(unsigned* p, unsigned v) { asm volatile("st.relaxed.gpu.global.u32 [%0], %1;" ::"l"(p), "r"(v) : "memory"); }
DI void red_xor(unsigned* p, unsigned v) { asm volatile("red.relaxed.gpu.global.xor.b32 [%0], %1;" ::"l"(p), "r"(v) : "memory"); }
DI unsigned ld_rlx(const unsigned* p) { unsigned v; asm volatile("ld.relaxed.gpu.global.u32 %0, [%1];" : "=r"(v) : "l"(p) : "memory"); return v; }
DI void publish(unsigned* p) { asm volatile("red.release.gpu.global.add.u32 [%0], 1;" ::"l"(p) : "memory"); }
DI void poll(const unsigned* p, unsigned ep) {
    asm volatile("{\n.reg .pred p;\n.reg .u32 v;\n"
                 "PL: ld.acquire.gpu.global.u32 v, [%0];\nsetp.eq.u32 p, v, %1;\nvote.sync.all.pred p, p, 0xffffffff;\n@!p bra.uni PL;\n}" ::"l"(p), "r"(ep) : "memory");
}
DI unsigned pollb(const unsigned* p, unsigned ep, unsigned mask) {
    unsigned v;
    asm volatile("{\n.reg .pred p;\n.reg .u32 n, t;\nmov.u32 n, 0;\n"
                 "PL: ld.acquire.gpu.global.u32 %0, [%1];\nand.b32 t, %0, %3;\nsetp.eq.u32 p, t, %2;\nvote.sync.all.pred p, p, 0xffffffff;\n@p bra.uni PD;\n"
                 "add.u32 n, n, 1;\nsetp.lt.u32 p, n, 2000000;\n@p bra.uni PL;\ntrap;\nPD:\n}" : "=&r"(v) : "l"(p), "r"(ep), "r"(mask) : "memory");
    return v;
}
DI void tma2d(uint32_t dst, const CUtensorMap* m, int c0, int c1, uint32_t bar) {
    asm volatile("cp.async.bulk.tensor.2d.shared::cluster.global.mbarrier::complete_tx::bytes [%0], [%1, {%3,%4}], [%2];" ::"r"(dst), "l"(m), "r"(bar), "r"(c0), "r"(c1) : "memory");
}
DI void tma2d_mc(uint32_t dst, const CUtensorMap* m, int c0, int c1, uint32_t bar) {
    asm volatile("cp.async.bulk.tensor.2d.shared::cluster.global.mbarrier::complete_tx::bytes.multicast::cluster [%0], [%1, {%3,%4}], [%2], %5;" ::"r"(dst), "l"(m), "r"(bar), "r"(c0), "r"(c1), "h"((unsigned short)3) : "memory");
}
DI void tma3d(uint32_t dst, const CUtensorMap* m, int c0, int c1, int c2, uint32_t bar) {
    asm volatile("cp.async.bulk.tensor.3d.shared::cluster.global.mbarrier::complete_tx::bytes [%0], [%1, {%3,%4,%5}], [%2];" ::"r"(dst), "l"(m), "r"(bar), "r"(c0), "r"(c1), "r"(c2) : "memory");
}
DI void tma3d_mc(uint32_t dst, const CUtensorMap* m, int c0, int c1, int c2, uint32_t bar) {
    asm volatile("cp.async.bulk.tensor.3d.shared::cluster.global.mbarrier::complete_tx::bytes.multicast::cluster [%0], [%1, {%3,%4,%5}], [%2], %6;" ::"r"(dst), "l"(m), "r"(bar), "r"(c0), "r"(c1), "r"(c2), "h"((unsigned short)3) : "memory");
}
DI void bulk_ld(uint32_t dst, const void* src, uint32_t bytes, uint32_t bar) {
    asm volatile("cp.async.bulk.shared::cluster.global.mbarrier::complete_tx::bytes [%0], [%1], %2, [%3];" ::"r"(dst), "l"(src), "r"(bytes), "r"(bar) : "memory");
}
DI void bulk_ld_mc(uint32_t dst, const void* src, uint32_t bytes, uint32_t bar) {
    asm volatile("cp.async.bulk.shared::cluster.global.mbarrier::complete_tx::bytes.multicast::cluster [%0], [%1], %2, [%3], %4;" ::"r"(dst), "l"(src), "r"(bytes), "r"(bar), "h"((unsigned short)3) : "memory");
}
DI void l2_prefetch(const void* p, uint32_t bytes) { asm volatile("cp.async.bulk.prefetch.L2.global [%0], %1;" ::"l"(p), "r"(bytes) : "memory"); }
DI void st_async(uint32_t dst, const uint32_t (&v)[4], uint32_t bar) {
    asm volatile("st.async.shared::cluster.mbarrier::complete_tx::bytes.v4.b32 [%0], {%1,%2,%3,%4}, [%5];" ::"r"(dst), "r"(v[0]), "r"(v[1]), "r"(v[2]), "r"(v[3]), "r"(bar) : "memory");
}
#define FENCE_ASYNC_S() asm volatile("fence.proxy.async.shared::cta;" ::: "memory")
#define FENCE_ASYNC_G() asm volatile("fence.proxy.async.global;" ::: "memory")
#define WG_FENCE() asm volatile("wgmma.fence.sync.aligned;" ::: "memory")
#define WG_COMMIT() asm volatile("wgmma.commit_group.sync.aligned;" ::: "memory")
#define WG_WAIT(n) asm volatile("wgmma.wait_group.sync.aligned %0;" ::"n"(n) : "memory")
template <int N> DI void pin(float (&d)[N]) {
#pragma unroll
    for (int i = 0; i < N; i++) asm volatile("" : "+f"(d[i])::"memory");
}
constexpr uint32_t SM_BASE = 1024;
DI uint64_t mkdesc(uint32_t off16, uint32_t off, uint32_t lbo) {
    uint32_t lo = off16 + (((SM_BASE + off) >> 4) | ((lbo >> 4) << 16));
    uint64_t d; asm("mov.b64 %0, {%1, %2};" : "=l"(d) : "r"(lo), "r"(0x40000040u)); return d;
}
DI uint32_t hadd2(uint32_t a, uint32_t b) { uint32_t d; asm("add.rn.bf16x2 %0, %1, %2;" : "=r"(d) : "r"(a), "r"(b)); return d; }
DI uint32_t hmul2(uint32_t a, uint32_t b) { uint32_t d; asm("mul.rn.bf16x2 %0, %1, %2;" : "=r"(d) : "r"(a), "r"(b)); return d; }
DI uint32_t hfma2(uint32_t a, uint32_t b, uint32_t c) { uint32_t d; asm("fma.rn.bf16x2 %0, %1, %2, %3;" : "=r"(d) : "r"(a), "r"(b), "r"(c)); return d; }
DI void wgmma_n8(float (&d)[4], uint64_t da, uint64_t db, int sc) {
    asm volatile("{\n.reg .pred p;\nsetp.ne.b32 p, %6, 0;\nwgmma.mma_async.sync.aligned.m64n8k16.f32.bf16.bf16 {%0,%1,%2,%3}, %4, %5, p, 1, 1, 1, 0;\n}"
                 : "+f"(d[0]), "+f"(d[1]), "+f"(d[2]), "+f"(d[3]) : "l"(da), "l"(db), "r"(sc));
}
DI void wgmma_rs_n8(float (&d)[4], const uint32_t (&a)[4], uint64_t db, int sc) {
    asm volatile("{\n.reg .pred p;\nsetp.ne.b32 p, %9, 0;\nwgmma.mma_async.sync.aligned.m64n8k16.f32.bf16.bf16 {%0,%1,%2,%3}, {%4,%5,%6,%7}, %8, p, 1, 1, 0;\n}"
                 : "+f"(d[0]), "+f"(d[1]), "+f"(d[2]), "+f"(d[3]) : "r"(a[0]), "r"(a[1]), "r"(a[2]), "r"(a[3]), "l"(db), "r"(sc));
}
__device__ __forceinline__ void wgmma_ss_n64(float (&d)[32], uint64_t da, uint64_t db, int sc){
  asm volatile("{.reg .pred p; setp.ne.b32 p, %34, 0;\n wgmma.mma_async.sync.aligned.m64n64k16.f32.bf16.bf16 {%0,%1,%2,%3,%4,%5,%6,%7,%8,%9,%10,%11,%12,%13,%14,%15,%16,%17,%18,%19,%20,%21,%22,%23,%24,%25,%26,%27,%28,%29,%30,%31}, %32, %33, p, 1, 1, 0, 1;}\n"
   : "+f"(d[0]),"+f"(d[1]),"+f"(d[2]),"+f"(d[3]),"+f"(d[4]),"+f"(d[5]),"+f"(d[6]),"+f"(d[7]),"+f"(d[8]),"+f"(d[9]),"+f"(d[10]),"+f"(d[11]),"+f"(d[12]),"+f"(d[13]),"+f"(d[14]),"+f"(d[15]),"+f"(d[16]),"+f"(d[17]),"+f"(d[18]),"+f"(d[19]),"+f"(d[20]),"+f"(d[21]),"+f"(d[22]),"+f"(d[23]),"+f"(d[24]),"+f"(d[25]),"+f"(d[26]),"+f"(d[27]),"+f"(d[28]),"+f"(d[29]),"+f"(d[30]),"+f"(d[31])
   : "l"(da),"l"(db),"r"(sc));
}
__device__ __forceinline__ void wgmma_ss_n96(float (&d)[48], uint64_t da, uint64_t db, int sc){
  asm volatile("{.reg .pred p; setp.ne.b32 p, %50, 0;\n wgmma.mma_async.sync.aligned.m64n96k16.f32.bf16.bf16 {%0,%1,%2,%3,%4,%5,%6,%7,%8,%9,%10,%11,%12,%13,%14,%15,%16,%17,%18,%19,%20,%21,%22,%23,%24,%25,%26,%27,%28,%29,%30,%31,%32,%33,%34,%35,%36,%37,%38,%39,%40,%41,%42,%43,%44,%45,%46,%47}, %48, %49, p, 1, 1, 0, 1;}\n"
   : "+f"(d[0]),"+f"(d[1]),"+f"(d[2]),"+f"(d[3]),"+f"(d[4]),"+f"(d[5]),"+f"(d[6]),"+f"(d[7]),"+f"(d[8]),"+f"(d[9]),"+f"(d[10]),"+f"(d[11]),"+f"(d[12]),"+f"(d[13]),"+f"(d[14]),"+f"(d[15]),"+f"(d[16]),"+f"(d[17]),"+f"(d[18]),"+f"(d[19]),"+f"(d[20]),"+f"(d[21]),"+f"(d[22]),"+f"(d[23]),"+f"(d[24]),"+f"(d[25]),"+f"(d[26]),"+f"(d[27]),"+f"(d[28]),"+f"(d[29]),"+f"(d[30]),"+f"(d[31]),"+f"(d[32]),"+f"(d[33]),"+f"(d[34]),"+f"(d[35]),"+f"(d[36]),"+f"(d[37]),"+f"(d[38]),"+f"(d[39]),"+f"(d[40]),"+f"(d[41]),"+f"(d[42]),"+f"(d[43]),"+f"(d[44]),"+f"(d[45]),"+f"(d[46]),"+f"(d[47])
   : "l"(da),"l"(db),"r"(sc));
}
__device__ __forceinline__ void wgmma_ss_n128(float (&d)[64], uint64_t da, uint64_t db, int sc){
  asm volatile("{.reg .pred p; setp.ne.b32 p, %66, 0;\n wgmma.mma_async.sync.aligned.m64n128k16.f32.bf16.bf16 {%0,%1,%2,%3,%4,%5,%6,%7,%8,%9,%10,%11,%12,%13,%14,%15,%16,%17,%18,%19,%20,%21,%22,%23,%24,%25,%26,%27,%28,%29,%30,%31,%32,%33,%34,%35,%36,%37,%38,%39,%40,%41,%42,%43,%44,%45,%46,%47,%48,%49,%50,%51,%52,%53,%54,%55,%56,%57,%58,%59,%60,%61,%62,%63}, %64, %65, p, 1, 1, 0, 1;}\n"
   : "+f"(d[0]),"+f"(d[1]),"+f"(d[2]),"+f"(d[3]),"+f"(d[4]),"+f"(d[5]),"+f"(d[6]),"+f"(d[7]),"+f"(d[8]),"+f"(d[9]),"+f"(d[10]),"+f"(d[11]),"+f"(d[12]),"+f"(d[13]),"+f"(d[14]),"+f"(d[15]),"+f"(d[16]),"+f"(d[17]),"+f"(d[18]),"+f"(d[19]),"+f"(d[20]),"+f"(d[21]),"+f"(d[22]),"+f"(d[23]),"+f"(d[24]),"+f"(d[25]),"+f"(d[26]),"+f"(d[27]),"+f"(d[28]),"+f"(d[29]),"+f"(d[30]),"+f"(d[31]),"+f"(d[32]),"+f"(d[33]),"+f"(d[34]),"+f"(d[35]),"+f"(d[36]),"+f"(d[37]),"+f"(d[38]),"+f"(d[39]),"+f"(d[40]),"+f"(d[41]),"+f"(d[42]),"+f"(d[43]),"+f"(d[44]),"+f"(d[45]),"+f"(d[46]),"+f"(d[47]),"+f"(d[48]),"+f"(d[49]),"+f"(d[50]),"+f"(d[51]),"+f"(d[52]),"+f"(d[53]),"+f"(d[54]),"+f"(d[55]),"+f"(d[56]),"+f"(d[57]),"+f"(d[58]),"+f"(d[59]),"+f"(d[60]),"+f"(d[61]),"+f"(d[62]),"+f"(d[63])
   : "l"(da),"l"(db),"r"(sc));
}
__device__ __forceinline__ void wgmma_rs_n64(float (&d)[32], const uint32_t (&a)[4], uint64_t db, int sc){
  asm volatile("{.reg .pred p; setp.ne.b32 p, %37, 0;\n wgmma.mma_async.sync.aligned.m64n64k16.f32.bf16.bf16 {%0,%1,%2,%3,%4,%5,%6,%7,%8,%9,%10,%11,%12,%13,%14,%15,%16,%17,%18,%19,%20,%21,%22,%23,%24,%25,%26,%27,%28,%29,%30,%31}, {%32,%33,%34,%35}, %36, p, 1, 1, 1;}\n"
   : "+f"(d[0]),"+f"(d[1]),"+f"(d[2]),"+f"(d[3]),"+f"(d[4]),"+f"(d[5]),"+f"(d[6]),"+f"(d[7]),"+f"(d[8]),"+f"(d[9]),"+f"(d[10]),"+f"(d[11]),"+f"(d[12]),"+f"(d[13]),"+f"(d[14]),"+f"(d[15]),"+f"(d[16]),"+f"(d[17]),"+f"(d[18]),"+f"(d[19]),"+f"(d[20]),"+f"(d[21]),"+f"(d[22]),"+f"(d[23]),"+f"(d[24]),"+f"(d[25]),"+f"(d[26]),"+f"(d[27]),"+f"(d[28]),"+f"(d[29]),"+f"(d[30]),"+f"(d[31])
   : "r"(a[0]),"r"(a[1]),"r"(a[2]),"r"(a[3]),"l"(db),"r"(sc));
}
__device__ __forceinline__ void wgmma_rs_n128(float (&d)[64], const uint32_t (&a)[4], uint64_t db, int sc){
  asm volatile("{.reg .pred p; setp.ne.b32 p, %69, 0;\n wgmma.mma_async.sync.aligned.m64n128k16.f32.bf16.bf16 {%0,%1,%2,%3,%4,%5,%6,%7,%8,%9,%10,%11,%12,%13,%14,%15,%16,%17,%18,%19,%20,%21,%22,%23,%24,%25,%26,%27,%28,%29,%30,%31,%32,%33,%34,%35,%36,%37,%38,%39,%40,%41,%42,%43,%44,%45,%46,%47,%48,%49,%50,%51,%52,%53,%54,%55,%56,%57,%58,%59,%60,%61,%62,%63}, {%64,%65,%66,%67}, %68, p, 1, 1, 1;}\n"
   : "+f"(d[0]),"+f"(d[1]),"+f"(d[2]),"+f"(d[3]),"+f"(d[4]),"+f"(d[5]),"+f"(d[6]),"+f"(d[7]),"+f"(d[8]),"+f"(d[9]),"+f"(d[10]),"+f"(d[11]),"+f"(d[12]),"+f"(d[13]),"+f"(d[14]),"+f"(d[15]),"+f"(d[16]),"+f"(d[17]),"+f"(d[18]),"+f"(d[19]),"+f"(d[20]),"+f"(d[21]),"+f"(d[22]),"+f"(d[23]),"+f"(d[24]),"+f"(d[25]),"+f"(d[26]),"+f"(d[27]),"+f"(d[28]),"+f"(d[29]),"+f"(d[30]),"+f"(d[31]),"+f"(d[32]),"+f"(d[33]),"+f"(d[34]),"+f"(d[35]),"+f"(d[36]),"+f"(d[37]),"+f"(d[38]),"+f"(d[39]),"+f"(d[40]),"+f"(d[41]),"+f"(d[42]),"+f"(d[43]),"+f"(d[44]),"+f"(d[45]),"+f"(d[46]),"+f"(d[47]),"+f"(d[48]),"+f"(d[49]),"+f"(d[50]),"+f"(d[51]),"+f"(d[52]),"+f"(d[53]),"+f"(d[54]),"+f"(d[55]),"+f"(d[56]),"+f"(d[57]),"+f"(d[58]),"+f"(d[59]),"+f"(d[60]),"+f"(d[61]),"+f"(d[62]),"+f"(d[63])
   : "r"(a[0]),"r"(a[1]),"r"(a[2]),"r"(a[3]),"l"(db),"r"(sc));
}

struct C2 { float r, i; };
DI C2 cmul(C2 a, C2 b) { C2 o; o.r = fmaf(a.r, b.r, -a.i * b.i); o.i = fmaf(a.r, b.i, a.i * b.r); return o; }
DI C2 cpow(float a2, float th, float l) {
    float m; asm("ex2.approx.ftz.f32 %0, %1;" : "=f"(m) : "f"(a2 * l));
    float ph = th * l; ph -= rintf(ph); ph *= 6.283185307179586f;
    C2 o; o.r = m * __cosf(ph); o.i = m * __sinf(ph); return o;
}
constexpr float GK0 = 0.7978845608028654f, GK1 = 0.044715f;
DI uint32_t gelu_tail(uint32_t y, uint32_t A, uint32_t B) {
    uint32_t u = hmul2(y, hfma2(hmul2(y, y), A, B)), t;
    asm("tanh.approx.bf16x2 %0, %1;" : "=r"(t) : "r"(u));
    return hfma2(y, t, y);
}
DI void row_stats(float s, float q, float& mu, float& r, float eps = 1e-5f) {
    mu = s * (1.f / 512);
    asm("rsqrt.approx.ftz.f32 %0, %1;" : "=f"(r) : "f"(fmaxf(q * (1.f / 512) - mu * mu, 0.f) + eps));
}
struct RowC { uint32_t nmu, A, B; };
DI RowC rowc(float mu, float r) { RowC c; float B = GK0 * r, A = GK1 * B * r * r; c.nmu = pk(-mu, -mu); c.A = pk(A, A); c.B = pk(B, B); return c; }
template <int N> DI void gelu16(const float (&acc)[N], int i, uint32_t vaddr, const RowC& lo, const RowC& hi, uint32_t (&o)[4]) {
    uint2 v = lds64(vaddr);
    o[0] = gelu_tail(hfma2(v.x, lo.nmu, pk(acc[8 * i + 0], acc[8 * i + 1])), lo.A, lo.B);
    o[1] = gelu_tail(hfma2(v.x, hi.nmu, pk(acc[8 * i + 2], acc[8 * i + 3])), hi.A, hi.B);
    o[2] = gelu_tail(hfma2(v.y, lo.nmu, pk(acc[8 * i + 4], acc[8 * i + 5])), lo.A, lo.B);
    o[3] = gelu_tail(hfma2(v.y, hi.nmu, pk(acc[8 * i + 6], acc[8 * i + 7])), hi.A, hi.B);
}
template <int N> DI void gelu16a(const float (&acc)[N], int i, uint2 v, const RowC& lo, const RowC& hi, uint32_t (&y)[4], uint32_t (&u)[4]) {
    y[0] = hfma2(v.x, lo.nmu, pk(acc[8 * i + 0], acc[8 * i + 1])); y[1] = hfma2(v.x, hi.nmu, pk(acc[8 * i + 2], acc[8 * i + 3]));
    y[2] = hfma2(v.y, lo.nmu, pk(acc[8 * i + 4], acc[8 * i + 5])); y[3] = hfma2(v.y, hi.nmu, pk(acc[8 * i + 6], acc[8 * i + 7]));
#pragma unroll
    for (int k = 0; k < 4; k++) u[k] = hmul2(y[k], hfma2(hmul2(y[k], y[k]), (k & 1) ? hi.A : lo.A, (k & 1) ? hi.B : lo.B));
}
DI void gelu16b(const uint32_t (&y)[4], const uint32_t (&u)[4], uint32_t (&o)[4]) {
#pragma unroll
    for (int k = 0; k < 4; k++) { uint32_t t; asm("tanh.approx.bf16x2 %0, %1;" : "=r"(t) : "r"(u[k])); o[k] = hfma2(y[k], t, y[k]); }
}
DI float qsum(float v) { v += __shfl_xor_sync(~0u, v, 1); v += __shfl_xor_sync(~0u, v, 2); return v; }
DI void ln_rows(const uint4 (&v)[4], int lane, unsigned* dst, unsigned ep) {
    float s[2], q[2];
#pragma unroll
    for (int r = 0; r < 2; r++) {
        s[r] = 0.f; q[r] = 0.f;
#pragma unroll
        for (int j = 0; j < 2; j++) {
            const uint4 w = v[2 * r + j];
            const uint32_t a = hadd2(hadd2(w.x, w.y), hadd2(w.z, w.w)), c = hfma2(w.w, w.w, hfma2(w.z, w.z, hfma2(w.y, w.y, hmul2(w.x, w.x))));
            s[r] += blo(a) + bhi(a); q[r] += blo(c) + bhi(c);
        }
    }
    bool u = lane & 16;
    float ss = (u ? s[1] : s[0]) + __shfl_xor_sync(~0u, u ? s[0] : s[1], 16);
    float qq = (u ? q[1] : q[0]) + __shfl_xor_sync(~0u, u ? q[0] : q[1], 16);
#pragma unroll
    for (int o = 8; o; o >>= 1) { ss += __shfl_xor_sync(~0u, ss, o); qq += __shfl_xor_sync(~0u, qq, o); }
    float mu, r; row_stats(ss, qq, mu, r); r = rbf(r);
    asm volatile("{\n.reg .pred p;\nsetp.eq.u32 p, %2, 0;\n@p red.relaxed.gpu.global.xor.b32 [%0], %1;\n}" ::"l"(dst), "r"(pk(-mu * r, r) | 0x80000000u), "r"(lane & 15) : "memory");
}
template <int W> DI void conv_near(float (&acc)[8][4], uint32_t ua, uint32_t n1, uint32_t n2) {
#pragma unroll(W ? 2 : 4)
    for (int r = 0; r < 8; r++) {
        uint32_t u[12][2];
#pragma unroll
        for (int i = 5; i >= (W ? 0 : 2); i--) ldsm4(ua + i * 256, u[2 * i][0], u[2 * i][1], u[2 * i + 1][0], u[2 * i + 1][1]);
#pragma unroll
        for (int q = 0; q < 5; q++) {
            if (q < 4 || r < 2) {
                const uint2 a = lds64(n1 + q * 64), e = lds64(n2 + q * 64);
#pragma unroll
                for (int j = 7; j >= (W ? 0 : q); j--) mma(acc[j], a.x, a.y, e.x, e.y, u[j - q + 4][0], u[j - q + 4][1]);
            }
        }
        ua -= 16; n1 += 8; n2 += 8;
    }
}
template <int W> DI void conv_far(float (&acc)[8][4], uint32_t bx, int ph, uint32_t ft) {
#pragma unroll
    for (int gi = 0; gi < 4; gi++) {
        const uint32_t aa = bx + ((gi & 1) ? B5_O : B3_O) + ((gi >> 1) ? (ph ^ 1) * (H2O - 16) : ph * H2O);
        uint32_t a[6][4]; uint2 f[6];
#pragma unroll
        for (int k = 0; k < (W ? 6 : 2); k++) ldsm4t(aa + k * 256, a[k][0], a[k][1], a[k][2], a[k][3]);
#pragma unroll
        for (int i = 0; i < (W ? 6 : 4); i++) f[i] = lds64(ft + gi * 448 + i * 64);
#pragma unroll
        for (int t = 0; t < 3; t++)
#pragma unroll
            for (int j = 7; j >= 0; j--) {
                const int k = (j >> 1) + 4 * W - 2 - t, i = 2 * t + (j & 1);
                if (k >= 0) mma(acc[j], a[k][0], a[k][1], a[k][2], a[k][3], f[i].x, f[i].y);
            }
    }
    if (W) {
#pragma unroll
        for (int gi = 0; gi < 3; gi++) {
            const uint32_t aa = bx + B9_O + gi * 2176 + (gi == 0 ? (ph ^ 1) * (H3O - 16) : ph * H3O);
            uint32_t a[4][4]; uint2 f[8];
#pragma unroll
            for (int k = 0; k < 4; k++) ldsm4t(aa + k * 256, a[k][0], a[k][1], a[k][2], a[k][3]);
#pragma unroll
            for (int i = 0; i < (gi < 2 ? 8 : 2); i++) f[i] = lds64(ft + 1792 + gi * 576 + i * 64);
#pragma unroll
            for (int t = 0; t < (gi < 2 ? 4 : 1); t++)
#pragma unroll
                for (int j = 7; j >= 2 * t; j--) {
                    const int k = (j >> 1) - t, i = 2 * t + (j & 1);
                    mma(acc[j], a[k][0], a[k][1], a[k][2], a[k][3], f[i].x, f[i].y);
                }
        }
    }
}

__global__ void __launch_bounds__(384, 1) __cluster_dims__(2, 1, 1)
fused_kernel(const __grid_constant__ Params P, const __grid_constant__ Maps M) {
    extern __shared__ __align__(1024) unsigned char smem_raw[];
    const uint32_t sm = (uint32_t)__cvta_generic_to_shared(smem_raw);
    const int ba = blockIdx.x;
    if (threadIdx.x < 64) {
        const int i = threadIdx.x >> 3;
        asm volatile("prefetch.global.L2 [%0];" ::"l"(P.par[i] + (i < 6 ? ba * 512 + (threadIdx.x & 7) * 64 : ba * 4)));
    }
    const uint32_t bars = sm + O_BAR;
#define ZG(u) (((gg ^ ((u) >> 1)) & 1) + 2 * ((u) & 1))
#define BAR(i) (bars + 8u * (uint32_t)(i))
#define WARRIVE_N(i, n) do { __syncwarp(); if (lane == 0) marrive_n(BAR(i), n); } while (0)
#define WARRIVE(i) do { __syncwarp(); if (lane == 0) marrive(BAR(i)); } while (0)
    const int cl = blockIdx.x >> 1, cb = cl - 36, col = cl < 4 ? 0 : cl < 36 ? (cl - 4) & 7 : cb % 7 + 1, row = cl < 4 ? 4 + cl : cl < 36 ? (cl - 4) >> 3 : 4 + cb / 7;
    const int b = (row * 2 + (col & 1)) * 8 + (col >> 1) * 2 + (blockIdx.x & 1), tid = __shfl_xor_sync(~0u, ((int)threadIdx.x - 128) ^ 129, 1), lane = tid & 31;
    const int warp = __shfl_sync(~0u, (((int)threadIdx.x - 128) ^ 128) >> 5, 0), wg = warp >> 2, wq = warp & 3, t128 = tid & 127;
    const int g = lane >> 2, c = lane & 3;
    const int p = b & 1, kq = (b >> 1) & 3, hh = kq >> 1, gg = 2 * p + (kq & 1), tau = 2 * (b >> 3) + hh, fj = b & 7;

    if (wg >= 0) {
        const int ch = wq;
        unsigned ep;
        float dskip;
        {
            if (warp == 0 && elect()) {
                asm volatile("mbarrier.init.shared::cta.b64 [%0], 1;\nmbarrier.init.shared::cta.b64 [%0+8], 1;\n"
                             "mbarrier.arrive.expect_tx.shared::cta.b64 _, [%0], 6176;\nmbarrier.arrive.expect_tx.shared::cta.b64 _, [%0+8], 16384;\n"
                             "fence.mbarrier_init.release.cluster;" ::"r"(BAR(B_PAR)) : "memory");
#pragma unroll
                for (int i = 0; i < 6; i++) bulk_ld(sm + O_PAR + i * 1024, P.par[i] + ba * 512, 1024, BAR(B_PAR));
#pragma unroll
                for (int i = 0; i < 2; i++) bulk_ld(sm + O_PAR + 6144 + i * 16, P.par[6 + i] + (ba >> 1) * 8, 16, BAR(B_PAR));
                bulk_ld(sm + O_XR, P.x + ba * 8192, 16384, BAR(B_XR));
            }
            if (warp == 0) TS(53);
            ep = ld_rlx(P.s->epoch + (ba * 32 + lane));
            asm volatile("barrier.cluster.arrive.relaxed.aligned;" ::: "memory");
#pragma unroll
            for (int i = 0; i < 5; i++) sts128(sm + O_NT + (i < 4 ? i * 4096 : 4 * NT_CH - 4096) + tid * 16, 0, 0, 0, 0);
#pragma unroll
            for (int i = 0; i < 4; i++) sts128(sm + O_FT + (i < 3 ? i * 4096 : 4 * FT_CH - 4096) + tid * 16, 0, 0, 0, 0);
            asm volatile("barrier.cluster.wait.aligned;" ::: "memory");
            if (warp == 1 && elect()) {
                tma3d(sm + O_XG + p * 8192, &tmX, 8 * (ba >> 1), 0, 4 * p, BAR(B_XL));
                tma3d(sm + O_XG + 16384 + p * 8192, &tmX, 8 * (ba >> 1), 128, 4 * p, BAR(B_XL + 1));
            }
            if (warp == 0) TS(64);
            mwait(BAR(B_PAR));
            if (warp == 0) TS(61);
            const uint32_t pa = sm + O_PAR + ch * 256 + wg * 128 + lane * 4, pb = sm + O_PAR + 6144 + p * 8 + (ch >> 1) * 4;
            const uint32_t r_ldt = lds32(pb), r_are = lds32(pa), r_aim = lds32(pa + 1024), r_bre = lds32(pa + 2048), r_bim = lds32(pa + 3072),
                           r_cre = lds32(pa + 4096), r_cim = lds32(pa + 5120), r_dk = lds32(pb + 16);
            unsigned* stp = P.s->stats + ((wq >> 1) * 1024 + 8 * ba + 4 * wg + 2 * (wq & 1) + (lane >> 4));
            if ((lane & 15) == 0) st_rlx(stp, ep << 31);
            dskip = (ch & 1) ? bhi(r_dk) : blo(r_dk);
            const float dt = rbf(expf((ch & 1) ? bhi(r_ldt) : blo(r_ldt)));
            const uint32_t kst = sm + warp * KST_W, ka = kst + lane * 8;
            C2 w8[2], z1[2], h2[2], f[2], f2[2], f4[2], f6[2], a[2];
#pragma unroll
            for (int m = 0; m < 2; m++) {
                C2 B = {m ? bhi(r_bre) : blo(r_bre), m ? bhi(r_bim) : blo(r_bim)}, C = {m ? bhi(r_cre) : blo(r_cre), m ? bhi(r_cim) : blo(r_cim)};
                C2 cb = cmul(C, B); f[m].r = cb.r * dt; f[m].i = -cb.i * dt; a[m] = f[m];
            }
#define KSTORE(row, v) sts64(ka + (row) * KST_P, pk(v[0].r, v[0].i), pk(v[1].r, v[1].i))
#define KMUL(o, x, y) do { o[0] = cmul(x[0], y[0]); o[1] = cmul(x[1], y[1]); } while (0)
            KSTORE(32, f);
#pragma unroll
            for (int m = 0; m < 2; m++) {
                float a2 = dt * (m ? bhi(r_are) : blo(r_are)) * 1.4426950408889634f;
                float th = dt * (m ? bhi(r_aim) : blo(r_aim)) * 0.15915494309189535f;
                w8[m] = cpow(a2, th, 8.f); z1[m] = cpow(a2, -th, 1.f); h2[m] = cpow(a2, -th, 256.f);
            }
            KMUL(f, f, z1); KSTORE(33, f); KMUL(f2, f, z1); KSTORE(34, f2); KMUL(f, f2, z1); KSTORE(35, f);
            KMUL(f4, f, z1); KSTORE(36, f4); KMUL(f, f4, z1); KSTORE(37, f); KMUL(f6, f, z1); KSTORE(38, f6);
            KMUL(f, f6, z1); KSTORE(39, f);
            KMUL(f2, f2, h2); KSTORE(41, f2); KMUL(f6, f6, h2); KSTORE(43, f6);
            KMUL(a, a, h2); KSTORE(40, a); KMUL(f4, f4, h2); KSTORE(42, f4);
            KMUL(a, a, h2); KSTORE(44, a); KMUL(f4, f4, h2); KSTORE(45, f4);
            KMUL(a, a, h2); KSTORE(46, a); KMUL(f4, f4, h2); KSTORE(47, f4);
#pragma unroll 1
            for (int r = 48; r < 53; r++) { KMUL(a, a, h2); KSTORE(r, a); }
            {
                uint32_t pa[3][2], pb[3][2];
                KMUL(f, w8, w8); KMUL(f, f, f); KMUL(f, f, f); KMUL(f2, f, f); KMUL(f4, f2, f);
#pragma unroll
                for (int m = 0; m < 2; m++) {
                    pa[0][m] = pk(f[m].r, f[m].i); pb[0][m] = pk(-f[m].i, f[m].r); pa[1][m] = pk(f2[m].r, f2[m].i); pb[1][m] = pk(-f2[m].i, f2[m].r);
                    pa[2][m] = pk(f4[m].r, f4[m].i); pb[2][m] = pk(-f4[m].i, f4[m].r);
                }
                a[0] = C2{1.f, 0.f}; a[1] = a[0];
#pragma unroll 2
                for (int r = 0; r < 8; r++) {
                    const uint32_t q0 = pk(a[0].r, a[0].i), q1 = pk(a[1].r, a[1].i);
                    KMUL(a, a, w8);
                    sts64(ka + r * KST_P, q0, q1);
#pragma unroll
                    for (int i = 0; i < 3; i++)
                        sts64(ka + (r + 8 * i + 8) * KST_P, hfma2(__byte_perm(q0, 0, 0x1010), pa[i][0], hmul2(__byte_perm(q0, 0, 0x3232), pb[i][0])),
                              hfma2(__byte_perm(q1, 0, 0x1010), pa[i][1], hmul2(__byte_perm(q1, 0, 0x3232), pb[i][1])));
                }
            }
            if (warp == 0) TS(62);
            ep++;
            mwait(BAR(B_XR));
            uint4 xa[4];
#pragma unroll
            for (int i = 0; i < 4; i++) xa[i] = lds128(sm + O_XR + warp * 2048 + i * 512 + lane * 16);
            __syncwarp();
            float d[6][4];
#pragma unroll
            for (int i = 0; i < 6; i++) { d[i][0] = d[i][1] = d[i][2] = d[i][3] = 0.f; }
            const uint32_t aA = kst + (lane & 15) * KST_P + (lane >> 4) * 16;
            const uint32_t aB = kst + (32 + 8 * (lane >> 4) + (lane & 7)) * KST_P + ((lane >> 3) & 1) * 16;
            const uint32_t aC = kst + (48 + (lane & 7)) * KST_P + (lane >> 3) * 16;
#pragma unroll
            for (int k2 = 0; k2 < 4; k2++) {
                uint32_t t0, t1, t2, t3; ldsm4(aC + k2 * 64, t0, t1, t2, t3);
#pragma unroll
                for (int e = 0; e < 2; e++) {
                    uint32_t x0, x1, x2, x3, y0, y1, y2, y3, b0, b1, b2, b3;
                    ldsm4(aA + k2 * 64 + e * 32, x0, x1, x2, x3); ldsm4(aA + 16 * KST_P + k2 * 64 + e * 32, y0, y1, y2, y3);
                    ldsm4(aB + k2 * 64 + e * 32, b0, b1, b2, b3);
                    mma(d[0], x0, x1, x2, x3, b0, b1); mma(d[1], x0, x1, x2, x3, b2, b3); mma(d[2], x0, x1, x2, x3, e ? t2 : t0, e ? t3 : t1);
                    mma(d[3], y0, y1, y2, y3, b0, b1); mma(d[4], y0, y1, y2, y3, b2, b3); mma(d[5], y0, y1, y2, y3, e ? t2 : t0, e ? t3 : t1);
                }
                if (k2 == 0) { ln_rows(xa, lane, stp, ep); SCHED_FENCE(); }
            }
            __syncwarp();
#pragma unroll
            for (int i = 0; i < 6; i++) {
                uint32_t o = kst + ((i / 3) * 16 + g) * KP_P + (i % 3) * 32 + c * 8;
                stsf2(o, d[i][0], d[i][1]); stsf2(o + 8 * KP_P, d[i][2], d[i][3]);
            }
            WARRIVE(B_KP);
            if (warp == 0) TS(1);
        }
        uint32_t xt[4][4];
        float acc0[8][4];
        const int ph = (lane >> 3) & 1, mr = 8 * (lane >> 4) + (lane & 7), o = g - 2 * c;
        const uint32_t ua = sm + O_U + ch * U_CH + ph * U_H + (64 * wg - 24 + mr) * 16;
        const uint32_t na = sm + O_NT + ch * NT_CH + (o & 7) * NT_R, n1 = na + (o < 0 ? NT_B + 4 : 8), n2 = na + (o < 0 ? 0 : NT_B + 4);
        {
            uint2 xr[8];
            uint32_t st[8], bad;
            uint4 mc;
            mwait(BAR(B_XL + wg)); mwait(BAR(B_XG + wg));
#pragma unroll
            for (int j = 0; j < 8; j++) xr[j] = lds64(sm + O_XG + wg * 16384 + j * 2048 + t128 * 16 + p * 8);
            if (t128 == 0) asm volatile("mbarrier.arrive.shared::cluster.b64 _, [%0], 2;" ::"r"(mapa(BAR(B_XD), p ^ 1)) : "memory");
            if (wq == 0) TS(4 + wg);
            bool first = true;
            do {
#pragma unroll
                for (int j = 0; j < 2; j++)
                    asm volatile("ld.relaxed.gpu.global.v4.u32 {%0,%1,%2,%3}, [%4];" : "=r"(st[4 * j]), "=r"(st[4 * j + 1]), "=r"(st[4 * j + 2]), "=r"(st[4 * j + 3])
                                 : "l"(P.s->stats + (1024 * j + 4 * tid)) : "memory");
                if (first) {
                    first = false;
                    mwait(BAR(B_KP));
                    const uint32_t k0 = sm + ch * KST_W, k1 = k0 + 4 * KST_W, nt = sm + O_NT + ch * NT_CH + (2 + 32 * wg + lane) * 4;
                    float v[8], pv;
                    if (wg == 0) {
                        float4 p0 = ldsf4(k0 + lane * KP_P), p1 = ldsf4(k0 + lane * KP_P + 16), q0 = ldsf4(k1 + lane * KP_P), q1 = ldsf4(k1 + lane * KP_P + 16);
                        v[0] = p0.x + q0.x; v[1] = p0.y + q0.y; v[2] = p0.z + q0.z; v[3] = p0.w + q0.w;
                        v[4] = p1.x + q1.x; v[5] = p1.y + q1.y; v[6] = p1.z + q1.z; v[7] = p1.w + q1.w;
                        pv = __shfl_up_sync(~0u, v[7], 1);
                        if (lane == 0) { pv = 0.f; v[0] += dskip; }
                    } else {
                        float4 p0 = ldsf4(k0 + lane * KP_P + 32), q0 = ldsf4(k1 + lane * KP_P + 32);
                        uint32_t eo = lane == 0 ? 31 * KP_P + 28 : 48;
                        float ex = ldsf(k0 + eo) + ldsf(k1 + eo);
                        v[0] = v[1] = p0.x + q0.x; v[2] = p0.y + q0.y; v[3] = v[4] = v[5] = p0.z + q0.z; v[6] = p0.w + q0.w;
                        v[7] = __shfl_down_sync(~0u, v[0], 1); if (lane == 31) v[7] = ex;
                        pv = lane == 0 ? ex : v[0];
                        if (lane >= 24)
                            sts32(sm + O_NT + ch * NT_CH + 66 * 4 + c * NT_R + (g & 1) * NT_B, pk(c == 3 ? 0.f : ex, ex));
                    }
#pragma unroll
                    for (int i = 0; i < 8; i++) { const uint32_t t = pk(v[i], i ? v[i - 1] : pv); sts32(nt + i * NT_R, t); sts32(nt + i * NT_R + NT_B, t); }
                    if (wq == 0) TS(2 + wg);
#pragma unroll
                    for (int j = 0; j < 4; j++) {
                        xt[0][j] = __byte_perm(xr[2 * j].x, xr[2 * j + 1].x, 0x5410); xt[1][j] = __byte_perm(xr[2 * j].x, xr[2 * j + 1].x, 0x7632);
                        xt[2][j] = __byte_perm(xr[2 * j].y, xr[2 * j + 1].y, 0x5410); xt[3][j] = __byte_perm(xr[2 * j].y, xr[2 * j + 1].y, 0x7632);
                    }
#pragma unroll
                    for (int j = 0; j < 8; j++) { acc0[j][0] = acc0[j][1] = acc0[j][2] = acc0[j][3] = 0.f; }
                    mwait(BAR(B_MOD0));
                    if (wq == 0) TS(8 + wg);
                    mc = lds128(sm + O_ML);
                    if (wg == 0) sts128(sm + O_U + (2 * wq + (lane >> 4)) * U_H + (lane & 7) * 16, 0, 0, 0, 0);
                }
                bad = 0;
#pragma unroll
                for (int j = 0; j < 8; j++) { st[j] ^= ep << 31; bad |= st[j]; }
            } while (__any_sync(~0u, (int)bad < 0));
            if (wq == 0) TS(6 + wg);
            const uint32_t uo = sm + O_U + (t128 & 1) * U_H + (8 + 64 * wg + (t128 >> 1)) * 16;
            uint32_t r2[4], nm2[4];
#pragma unroll
            for (int j = 0; j < 4; j++) { r2[j] = __byte_perm(st[2 * j], st[2 * j + 1], 0x7632); nm2[j] = __byte_perm(st[2 * j], st[2 * j + 1], 0x5410); }
#pragma unroll
            for (int k = 0; k < 4; k++) {
                const uint32_t sel = (k & 1) ? 0x3232 : 0x1010, sa = __byte_perm((k & 2) ? mc.y : mc.x, 0, sel), c1 = __byte_perm((k & 2) ? mc.w : mc.z, 0, sel);
                sts128(uo + k * U_CH, hfma2(hfma2(xt[k][0], r2[0], nm2[0]), c1, sa), hfma2(hfma2(xt[k][1], r2[1], nm2[1]), c1, sa),
                       hfma2(hfma2(xt[k][2], r2[2], nm2[2]), c1, sa), hfma2(hfma2(xt[k][3], r2[3], nm2[3]), c1, sa));
            }
            WARRIVE(B_TAB);
        }
        {
            float (&acc)[8][4] = acc0;
            const uint32_t bx = sm + O_BOX + ch * BOX_CH + (mr + 1) * 16, ft = sm + O_FT + ch * FT_CH + (8 + o) * 8;
            nbar(3, 256);
            if (wg) {
                if (wq == 0) TS(11);
                conv_near<1>(acc, ua, n1, n2);
                if (wq == 0) TS(13);
                mwait(BAR(B_FAR + 1));
                if (wq == 0) TS(15);
                conv_far<1>(acc, bx, ph, ft);
            } else {
                if (wq == 0) TS(10);
                conv_near<0>(acc, ua, n1, n2);
                if (wq == 0) TS(12);
                mwait(BAR(B_FAR));
                if (wq == 0) TS(14);
                conv_far<0>(acc, bx, ph, ft);
            }
            if (wq == 0) TS(16 + wg);
            const uint32_t yb = wg ? sm + O_BOX + B9_O : sm + O_Y0, ych = wg ? BOX_CH : Y_CH;
            __syncwarp();
#pragma unroll
            for (int j = 0; j < 8; j += 2)
                stsm4t(yb + ch * ych + ph * H3O + (8 * j + mr) * 16, pk(acc[j][0], acc[j][1]), pk(acc[j][2], acc[j][3]),
                       pk(acc[j + 1][0], acc[j + 1][1]), pk(acc[j + 1][2], acc[j + 1][3]));
            mwait(BAR(B_MOD1));
            const uint4 gc = lds128(sm + O_ML + 16);
            nbar(1 + wg, 128);
            uint4 yq[4];
#pragma unroll
            for (int k = 0; k < 4; k++) yq[k] = lds128(yb + k * ych + (t128 & 1) * H3O + (t128 >> 1) * 16);
#pragma unroll
            for (int k = 0; k < 4; k++) {
                const uint32_t sel = (k & 1) ? 0x3232 : 0x1010, ga = __byte_perm((k & 2) ? gc.y : gc.x, 0, sel), c1 = __byte_perm((k & 2) ? gc.w : gc.z, 0, sel);
                stg128(P.s->xs + ((4 * ba + k) * 2048 + 8 * tid), make_uint4(hmul2(hfma2(ga, yq[k].x, xt[k][0]), c1), hmul2(hfma2(ga, yq[k].y, xt[k][1]), c1),
                                                                             hmul2(hfma2(ga, yq[k].z, xt[k][2]), c1), hmul2(hfma2(ga, yq[k].w, xt[k][3]), c1)));
            }
            if (wq == 0) TS(66 + wg);
            WARRIVE(B_CEND);
        }
        const uint32_t swz0 = sm + warp * 2048 + (lane & 15) * 128 + (((lane >> 4) ^ (lane & 7)) << 4);
#define SWZ(q) (swz0 ^ ((q) << 5))
        const uint32_t swt = sm + (8 * (lane >> 4) + (lane & 7)) * 128 + (((2 * wq + ((lane >> 3) & 1)) ^ (lane & 7)) << 4);
        uint32_t xs[16];
        float zac[32];
        if (wg == 0) {
            {
                uint32_t m[3][4], bad;
                do {
                    bad = 0;
#pragma unroll
                    for (int i = 0; i < 3; i++)
                        asm volatile("ld.relaxed.gpu.global.v4.u32 {%0,%1,%2,%3}, [%4];" : "=r"(m[i][0]), "=r"(m[i][1]), "=r"(m[i][2]), "=r"(m[i][3]) : "l"(P.s->modf + (512 * i + 4 * t128)) : "memory");
#pragma unroll
                    for (int i = 0; i < 12; i++) bad |= m[i >> 2][i & 3] ^ (ep | 0x80u);
                } while (__any_sync(~0u, bad & 0xffu));
                float ic[4];
#pragma unroll
                for (int i = 0; i < 4; i++) asm("rcp.approx.ftz.f32 %0, %1;" : "=f"(ic[i]) : "f"(bhi(m[1][i])));
                const uint32_t i0 = pk(ic[0], ic[1]), i1 = pk(ic[2], ic[3]), q0 = pk(ic[0] * ic[0], ic[1] * ic[1]), q1 = pk(ic[2] * ic[2], ic[3] * ic[3]), one = 0x3f803f80u;
                if (wq == gg) stsf4(sm + O_IC + lane * 16, ic[0], ic[1], ic[2], ic[3]);
                if ((wq >> 1) == p) {
                    const uint32_t a = sm + O_GB + (wq & 1) * 256 + (lane >> 2) * 32 + (lane & 1) * 16 + (lane & 2) * 2;
                    sts32(a, __byte_perm(m[2][0], m[2][1], 0x7632)); sts32(a + 8, __byte_perm(m[2][2], m[2][3], 0x7632));
                }
                float gs[5] = {0.f, 0.f, 0.f, 0.f, 0.f};
#pragma unroll
                for (int i = 0; i < 4; i++) {
                    const float cv = bhi(m[1][i]), sv = bhi(m[0][i]);
                    gs[0] += cv; gs[1] += sv; gs[2] = fmaf(cv, cv, gs[2]); gs[3] = fmaf(cv, sv, gs[3]); gs[4] = fmaf(sv, sv, gs[4]);
                }
#pragma unroll 1
                for (int d = 16; d; d >>= 1)
#pragma unroll
                    for (int i = 0; i < 5; i++) gs[i] += __shfl_xor_sync(~0u, gs[i], d);
                const uint32_t a = (sm + O_BT + (t128 >> 4) * 1024 + (t128 & 15) * 8);
                if (wq == 0) TS(18);
                mwait(BAR(B_CEND));
                stsf4(sm + O_GC + wq * 16, gs[0], gs[1], gs[2], gs[3]); stsf(sm + O_GC + 64 + wq * 4, gs[4]);
                sts64(a, i0, i1); sts64((a + 128) ^ 16, one, one);
                sts64((a + 256) ^ 32, __byte_perm(m[1][0], m[1][1], 0x7632), __byte_perm(m[1][2], m[1][3], 0x7632));
                sts64((a + 384) ^ 48, __byte_perm(m[0][0], m[0][1], 0x7632), __byte_perm(m[0][2], m[0][3], 0x7632));
                sts64((a + 512) ^ 64, q0, q1); sts64((a + 640) ^ 80, one, one);
                FENCE_ASYNC_S();
                WARRIVE(B_BT);
            }
        }
        {
            float d[4];
            mwait(BAR(B_BT)); mwait(BAR(B_W1 + wg));
#pragma unroll 1
            for (int s = 0; s < 4; s++) {
                WG_FENCE();
#pragma unroll
                for (int k = 0; k < 8; k++) wgmma_n8(d, mkdesc(wg * 4096 + s * 1024, k * 2048, 16), mkdesc(s * 128, O_BT + (k >> 2) * 1024 + (k & 3) * 32, 16), s | k);
                WG_COMMIT();
            }
            WG_WAIT(0); pin(d);
            const uint32_t a = O_VT + warp * 32 + (g >> 1) * 8 + (g & 1) * 2;
            if (c < 2) { *(bf16*)(smem_raw + a + 512 - 256 * c) = __float2bfloat16_rn(d[1]); *(bf16*)(smem_raw + a + 516 - 256 * c) = __float2bfloat16_rn(d[3]); }
            if (c == 1) { *(bf16*)(smem_raw + a) = __float2bfloat16_rn(d[0]); *(bf16*)(smem_raw + a + 4) = __float2bfloat16_rn(d[2]); }
            nbar(1 + wg, 128);
            if (warp == 4) TS(20);
        }
        {
            uint2 v1[4], v2[4], v3[4];
#pragma unroll
            for (int q = 0; q < 4; q++) { const uint32_t a = sm + O_VT + wg * 128 + q * 32 + c * 8; v1[q] = lds64(a); v2[q] = lds64(a + 256); v3[q] = lds64(a + 512); }
            float acc[32], dl[4], dq[4];
            uint32_t af[2][4][4];
#pragma unroll 1
            for (int s = 0; s < 2; s++) {
#pragma unroll
                for (int e = 0; e < 2; e++) {
                    uint32_t sq[4][4];
                    const int kb = 4 * wg + 2 * s + e;
                    mwait(BAR(B_HF + kb));
                    if (warp == 0 && s == 0 && e == 0) TS(22);
#pragma unroll
                    for (int k = 0; k < 4; k++) ldsm4t(swt + O_A + kb * 8192 + k * 2048, af[e][k][0], af[e][k][1], af[e][k][2], af[e][k][3]);
#pragma unroll
                    for (int k = 0; k < 16; k++) sq[k >> 2][k & 3] = hmul2(af[e][k >> 2][k & 3], af[e][k >> 2][k & 3]);
                    WG_FENCE();
#pragma unroll
                    for (int k = 0; k < 4; k++) { wgmma_rs_n8(dl, af[e][k], mkdesc(kb * 64, O_BT + k * 32, 16), s | e | k); wgmma_rs_n8(dq, sq[k], mkdesc(kb * 64, O_BT + k * 32, 16), s | e | k); }
                    WG_COMMIT();
#pragma unroll
                    for (int k = 0; k < 4; k++) wgmma_rs_n64(acc, af[e][k], mkdesc(wg * 4096 + kb * 512, k * 2048, 16), s | e | k);
                    WG_COMMIT();
                    if (s) { mwait(BAR(B_HF + 4 * (wg ^ 1) + 2 * e)); mwait(BAR(B_HF + 4 * (wg ^ 1) + 2 * e + 1)); }
                    WG_WAIT(1);
                    if (s == 1 && e == 0 && lane == 0) marrive_n(BAR(B_E1 + wg), 2);
                }
            }
            pin(dl); pin(dq);
            uint32_t ag[16][4];
            {
                const uint32_t a = sm + O_RP + (16 * warp + g) * 32 + c * 8;
                stsf2(a, c < 2 ? dl[0] : dq[0], c < 2 ? dl[1] : dq[1]); stsf2(a + 256, c < 2 ? dl[2] : dq[2], c < 2 ? dl[3] : dq[3]);
            }
            WARRIVE(B_RP);
#pragma unroll
            for (int k = 0; k < 8; k++) ldsm4t(swt + O_A + (wg ^ 1) * 32768 + k * 2048, ag[k][0], ag[k][1], ag[k][2], ag[k][3]);
#pragma unroll
            for (int s = 0; s < 2; s++) {
                WG_FENCE();
#pragma unroll
                for (int k = 0; k < 8; k++) wgmma_rs_n64(acc, ag[8 * s + k], mkdesc(2048 + wg * 2048, s * SLOT + k * 2048, 16), 1);
                WG_COMMIT();
                if (s == 0) {
#pragma unroll
                    for (int k = 8; k < 16; k++) ldsm4t(swt + O_A + (wg ^ 1) * 32768 + k * 2048, ag[k][0], ag[k][1], ag[k][2], ag[k][3]);
                }
                WG_WAIT(1);
                if (lane == 0) marrive_n(BAR(B_E1 + 2 + 2 * s + wg), 2);
            }
            mwait(BAR(B_RC));
            const uint4 c0 = lds128(sm + O_RC + (16 * wq + g) * 16), c1 = lds128(sm + O_RC + (16 * wq + g + 8) * 16);
            const float al0 = __uint_as_float(c0.x), al1 = __uint_as_float(c1.x);
            const uint32_t y0 = c0.y, y1 = c1.y, z0 = c0.z, z1 = c1.z, w0 = c0.w, w1 = c1.w;
            const uint32_t kA = pk(GK1 / (GK0 * GK0), GK1 / (GK0 * GK0)), kB = 0x3f803f80u;
            uint2 cr[2][4];
#pragma unroll
            for (int e = 0; e < 1; e++) {
                const uint32_t a1 = __byte_perm(e ? y1 : y0, 0, 0x1010), a2 = __byte_perm(e ? y1 : y0, 0, 0x3232), a3 = __byte_perm(e ? z1 : z0, 0, 0x1010);
#pragma unroll
                for (int q = 0; q < 4; q++) { cr[e][q].x = hfma2(v2[q].x, a2, hfma2(v1[q].x, a1, hmul2(v3[q].x, a3))); cr[e][q].y = hfma2(v2[q].y, a2, hfma2(v1[q].y, a1, hmul2(v3[q].y, a3))); }
            }
            bf16* ho = P.s->h + ((64 * tau + 16 * wq + (lane >> 3) + 2) * 512 + 128 * gg + 64 * wg + (lane & 7) * 8);
            SCHED_OPEN(ck1);
            WG_WAIT(0); pin(acc);
            if (warp == 0) TS(23);
            if (lane == 0) marrive_n(BAR(B_E1 + 6 + wg), 2);
#pragma unroll
            for (int q = 0; q < 4; q++) ldsm4t(swt + O_A + (2 * gg + wg) * 8192 + q * 2048, xs[4 * q], xs[4 * q + 1], xs[4 * q + 2], xs[4 * q + 3]);
#define H1PAIR(q, f, i) gelu_tail(hadd2(cr[e][q].f, pk(acc[8 * (q) + (i)] * al, acc[8 * (q) + (i) + 1] * al)), kA, kB)
            const uint32_t stg = sm + 12 * SLOT + warp * 2048;
#pragma unroll
            for (int e = 0; e < 2; e++) {
                const float al = e ? al1 : al0;
                const uint32_t sa = stg + e * 1024 + (lane & 7) * 128 + (((lane >> 3) ^ (lane & 7)) << 4);
                stsm4(sa, H1PAIR(0, x, 2 * e), H1PAIR(0, y, 4 + 2 * e), H1PAIR(1, x, 2 * e), H1PAIR(1, y, 4 + 2 * e));
                stsm4(sa ^ 64, H1PAIR(2, x, 2 * e), H1PAIR(2, y, 4 + 2 * e), H1PAIR(3, x, 2 * e), H1PAIR(3, y, 4 + 2 * e));
                if (e) FENCE_ASYNC_S();
                __syncwarp();
                const uint32_t la = stg + e * 1024 + (lane >> 3) * 128 + (((lane & 7) ^ (lane >> 3)) << 4);
                const uint4 t0 = lds128(la), t1 = lds128((la + 512) ^ 64);
                if (e != (gg & 1) && wq == 3 * e && (lane >> 4) == e) {
                    const uint4 t = e ? t1 : t0;
                    asm volatile("{\n.reg .b64 a, b;\nmov.b64 a, {%1, %5};\nmov.b64 b, {%2, %5};\nst.relaxed.gpu.global.v2.b64 [%0], {a, b};\n"
                                 "mov.b64 a, {%3, %5};\nmov.b64 b, {%4, %5};\nst.relaxed.gpu.global.v2.b64 [%0+16], {a, b};\n}"
                                 ::"l"(P.s->hl + ((tau * 4 + gg) * 64 + (lane & 8) * 4 + wg * 16 + (lane & 7) * 2)), "r"(t.x), "r"(t.y), "r"(t.z), "r"(t.w), "r"(ep) : "memory");
                }
                stg128(ho + e * 4096, t0); stg128(ho + e * 4096 + 2048, t1);
                if (e == 0) {
                SCHED_CLOSE(ck1);
#pragma unroll
            for (int e = 1; e < 2; e++) {
                const uint32_t a1 = __byte_perm(e ? y1 : y0, 0, 0x1010), a2 = __byte_perm(e ? y1 : y0, 0, 0x3232), a3 = __byte_perm(e ? z1 : z0, 0, 0x1010);
#pragma unroll
                for (int q = 0; q < 4; q++) { cr[e][q].x = hfma2(v2[q].x, a2, hfma2(v1[q].x, a1, hmul2(v3[q].x, a3))); cr[e][q].y = hfma2(v2[q].y, a2, hfma2(v1[q].y, a1, hmul2(v3[q].y, a3))); }
            }
                }
            }
            WARRIVE(B_PH);
            if (warp == 0) TS(25);
#pragma unroll
            for (int n = 0; n < 8; n++) {
                const uint32_t a = sm + O_BT + (2 * gg + wg) * 1024 + c * 4, cv = lds32(a + 256 + ((n ^ 2) << 4)), sv = lds32(a + 384 + ((n ^ 3) << 4));
                const uint32_t h0 = hfma2(xs[2 * n], __byte_perm(z0, 0, 0x3232), hfma2(cv, __byte_perm(w0, 0, 0x1010), sv));
                const uint32_t h1 = hfma2(xs[2 * n + 1], __byte_perm(z1, 0, 0x3232), hfma2(cv, __byte_perm(w1, 0, 0x1010), sv));
                zac[4 * n] = blo(h0) * (2.f * GK0); zac[4 * n + 1] = bhi(h0) * (2.f * GK0); zac[4 * n + 2] = blo(h1) * (2.f * GK0); zac[4 * n + 3] = bhi(h1) * (2.f * GK0);
            }
            SCHED_FENCE();
        }
        asm volatile("setmaxnreg.inc.sync.aligned.u32 232;");
        {
#pragma unroll
            for (int s = 0; s < 2; s++) {
                const int r = 16 * wq + (lane & 15) + ((gg & 1) ? 1 + (p ^ s) : -1 - (p ^ s));
                const bool in = (unsigned)r < 64u;
                const uint32_t a0 = in ? sm + (s ? O_A : 12 * SLOT) + r * 128 + (((lane >> 4) ^ (r & 7)) << 4) : sm + O_HB + s * 512 + (r & 1) * 256 + (lane & 16);
                const uint32_t a1 = a0 + (in ? 8192 : 128);
                uint32_t af[8][4];
                mwait(BAR(B_W2 + s)); mwait(BAR(B_HB)); mwait(BAR(s ? B_HP : B_PH));
                if (warp == 0) TS(29 + s);
#pragma unroll
                for (int k = 0; k < 8; k++) ldsm4((k < 4 ? a0 : a1) ^ ((k & 3) << 5), af[k][0], af[k][1], af[k][2], af[k][3]);
                WG_FENCE();
#pragma unroll
                for (int k = 0; k < 8; k++) wgmma_rs_n64(zac, af[k], mkdesc(wg * 6144 + s * 1024, k * 2048, 16), 1);
                WG_COMMIT();
                if (s == 0) WG_WAIT(0);
            }
            if (lane == 0) { marrive(BAR(B_E2)); if (wg) marrive_rem(mapa(BAR(B_HD), p ^ 1)); }
#pragma unroll 1
            for (int s = 2; s < 4; s++) {
                mwait(BAR(B_W2 + s));
#pragma unroll
                for (int e = 0; e < 2; e++) {
                    const int kb = 2 * s + (e ^ p);
                    mwait<1>(BAR(B_HF + kb));
                    if (wq == 0 && s == 2 && e == 0) TS(27 + wg);
                    WG_FENCE();
#pragma unroll
                    for (int k = 0; k < 4; k++)
                        wgmma_ss_n64(zac, mkdesc(kb * 512, O_A + k * 32, 16), mkdesc(wg * 2048 + kb * 512, k * 2048, 16), 1);
                }
                WG_COMMIT();
            }
            WG_WAIT(1);
            if (lane == 0) marrive(BAR(B_E2 + 1));
            mwait(BAR(B_E2));
            uint4* zo = P.s->z + ((tau * 8 + 2 * gg) * 512 + warp * 128 + lane);
            WG_WAIT(0); pin(zac);
            if (wq == 0) TS(31 + wg);
#pragma unroll
            for (int q = 0; q < 4; q++)
                stsm4(SWZ(q), pk(zac[8 * q], zac[8 * q + 1]), pk(zac[8 * q + 2], zac[8 * q + 3]), pk(zac[8 * q + 4], zac[8 * q + 5]), pk(zac[8 * q + 6], zac[8 * q + 7]));
            __syncwarp();
            uint4 t[4];
#pragma unroll
            for (int k = 0; k < 4; k++) t[k] = lds128(sm + warp * 2048 + k * 512 + lane * 16);
#pragma unroll
            for (int k = 0; k < 4; k++) stg128(zo + 32 * k, t[k]);
            WARRIVE(B_PZ);
            if (wq == 0) TS(33 + wg);
            mwait(BAR(B_PZ));
            if (wg == 0 && lane == 0) marrive_rem(mapa(BAR(B_PZP), p ^ 1));
#pragma unroll
            for (int q = 0; q < 4; q++)
                stsm4(SWZ(q) + (2 * p + hh) * SLOT, pk(zac[8 * q], zac[8 * q + 1]), pk(zac[8 * q + 2], zac[8 * q + 3]), pk(zac[8 * q + 4], zac[8 * q + 5]), pk(zac[8 * q + 6], zac[8 * q + 7]));
            FENCE_ASYNC_S();
            WARRIVE(B_ZL);
            SCHED_FENCE();
            float s0 = 0.f, q0 = 0.f, s1 = 0.f, q1 = 0.f;
#pragma unroll
            for (int n = 0; n < 8; n++) {
                s0 += zac[4 * n] + zac[4 * n + 1]; q0 = fmaf(zac[4 * n], zac[4 * n], fmaf(zac[4 * n + 1], zac[4 * n + 1], q0));
                s1 += zac[4 * n + 2] + zac[4 * n + 3]; q1 = fmaf(zac[4 * n + 2], zac[4 * n + 2], fmaf(zac[4 * n + 3], zac[4 * n + 3], q1));
            }
            { const bool u = c & 1;
              s0 = (u ? s1 : s0) + __shfl_xor_sync(~0u, u ? s0 : s1, 1); q0 = (u ? q1 : q0) + __shfl_xor_sync(~0u, u ? q0 : q1, 1);
              s0 += __shfl_xor_sync(~0u, s0, 2); q0 += __shfl_xor_sync(~0u, q0, 2); }
            if (c < 2) asm volatile("{\n.reg .b64 t;\nmov.b64 t, {%1, %2};\nst.relaxed.gpu.global.b64 [%0], t;\n}" ::"l"(P.s->zst + ((tau * 8 + 2 * gg) * 64 + 16 * warp + g + 8 * c)),
                                    "r"(__float_as_uint(s0)), "r"(((__float_as_uint(q0) + 0x80u) & 0xffffff00u) | (ep & 0xffu)) : "memory");
#pragma unroll
            for (int q = 0; q < 4; q++) {
                const uint2 gv = lds64(sm + O_GB + (gg & 1) * 256 + wg * 128 + q * 32 + c * 8);
                uint32_t o[4];
#pragma unroll
                for (int e = 0; e < 2; e++) {
                    const float2 ic = ldsf2(sm + O_IC + wg * 256 + q * 64 + e * 32 + c * 8);
                    const float g0 = blo(e ? gv.y : gv.x) * (0.5f / GK0), g1 = bhi(e ? gv.y : gv.x) * (0.5f / GK0);
#pragma unroll
                    for (int r = 0; r < 2; r++)
                        o[2 * e + r] = pk(fmaf(g0, zac[8 * q + 4 * e + 2 * r], blo(xs[4 * q + 2 * e + r]) * ic.x), fmaf(g1, zac[8 * q + 4 * e + 2 * r + 1], bhi(xs[4 * q + 2 * e + r]) * ic.y));
                }
                stsm4(SWZ(q) + 11 * SLOT, o[0], o[1], o[2], o[3]);
            }
            FENCE_ASYNC_S();
            WARRIVE(B_BA);
        }
        uint32_t Ho[14][4], Hp[14][4];
        float acc[64];
        uint32_t rp0, rp1, po[32];
        const uint32_t peer = p ^ 1;
#define W3A(i) ((uint32_t)((W3SLOT >> (4 * (i))) & 15) * SLOT)
#define W4A(i) ((uint32_t)((W4SLOT >> (4 * (i))) & 15) * SLOT)
#define G4PAIR(j, H, k0, first) do { \
            if (j) mwait(BAR(B_W4 + (j) / 2)); \
            WG_FENCE(); \
            _Pragma("unroll") \
            for (int k = 0; k < (((j) & 4) ? 6 : 8); k++) { \
                wgmma_rs_n128(acc, H[(k0) + k], mkdesc(0, W4A((j) + (k >> 2)) + (k & 3) * 2048, (((j) & 4) && k >= 4) ? 4096 : 8192), !(first) || k); \
                if (((j) & 7) == 6 && k == 3) WG_COMMIT(); } \
            WG_COMMIT(); } while (0)
#define G4PACK() _Pragma("unroll") for (int i = 0; i < 32; i++) po[i] = pk(acc[2 * i], acc[2 * i + 1])
        {
            float acc2[48];
            const float2* zs = P.s->zst + (((tau & ~1) + wg) * 512 + c * 128 + 16 * wq + g);
#define G3STEP(s) do { \
                mwait(BAR(B_W3 + (s))); mwait(BAR(((s) & 6) + wg == 2 * p + hh ? B_ZL : B_ZF + ((s) & 6) + wg)); \
                if (wq == 0 && (s) == 0) TS(35 + wg); \
                WG_FENCE(); \
                _Pragma("unroll") \
                for (int k = 0; k < 4; k++) \
                    wgmma_ss_n128(acc, mkdesc((((s) & 6) + wg) * 1024 + ((s) & 1) * 512, k * 32, 16), mkdesc((((uint32_t)W3SLOT >> (4 * (s))) & 15) * 1024, k * 2048, 8192), (s) | k); \
                WG_COMMIT(); \
                WG_WAIT(1); \
                if ((s) > 0 && lane == 0) marrive(BAR(B_ST + (s) - 1)); } while (0)
#pragma unroll 1
            for (int s = 0; s < 6; s++) G3STEP(s);
            uint2 t0 = ld_rlx64(zs), t1 = ld_rlx64(zs + 64), t2 = ld_rlx64(zs + 8), t3 = ld_rlx64(zs + 72);
            const uint32_t va = sm + O_V4 + c * 8;
            uint2 vv[8]; uint32_t gy[2][4], gu[2][4];
#pragma unroll
            for (int s = 0; s < 8; s++) vv[s] = lds64(va + s * 32);
            G3STEP(6);
            SCHED_OPEN(ck0);
            while (__any_sync(~0u, ((t0.y ^ ep) | (t1.y ^ ep) | (t2.y ^ ep) | (t3.y ^ ep)) & 0xffu)) { t0 = ld_rlx64(zs); t1 = ld_rlx64(zs + 64); t2 = ld_rlx64(zs + 8); t3 = ld_rlx64(zs + 72); }
            t0.y &= 0xffffff00u; t1.y &= 0xffffff00u; t2.y &= 0xffffff00u; t3.y &= 0xffffff00u;
            float m0, m1, rs0, rs1;
            row_stats(qsum(__uint_as_float(t0.x) + __uint_as_float(t1.x)), qsum(__uint_as_float(t0.y) + __uint_as_float(t1.y)), m0, rs0, 1e-5f * 4.f * GK0 * GK0);
            row_stats(qsum(__uint_as_float(t2.x) + __uint_as_float(t3.x)), qsum(__uint_as_float(t2.y) + __uint_as_float(t3.y)), m1, rs1, 1e-5f * 4.f * GK0 * GK0);
            const RowC lo = rowc(m0, rs0), hi = rowc(m1, rs1);
            rp0 = pk(0.5f * rs0, 0.5f * rs0); rp1 = pk(0.5f * rs1, 0.5f * rs1);
            SCHED_CLOSE(ck0);
            G3STEP(7);
            const uint32_t l0 = mapa(sm + wg * 8192 + t128 * 16, peer), lb0 = mapa(BAR(wg), peer);
#define HOFF(k) ((k) < 4 ? 11 * SLOT + (k) * 2048 : (k) < 8 ? ((k) - 4) * 2048 : (k) < 12 ? 4 * SLOT + ((k) - 8) * 2048 : 5 * SLOT + ((k) - 12) * 2048)
#define HSEND(k) st_async(l0 + HOFF(k), Ho[k], lb0 + 8 * ((k) < 8 ? B_LH0 : B_LH1))
#pragma unroll
            for (int s = 0; s < 8; s++) {
                if (s == 0) mwait(BAR(B_W3 + 8));
                WG_FENCE();
#pragma unroll
                for (int k = 0; k < 4; k++)
                    wgmma_ss_n96(acc2, mkdesc(wg * 1024, (s & 6) * SLOT + (s & 1) * 8192 + k * 32, 16), mkdesc(0, W3A(8 + s) + k * 2048, 8192 + 64), s | k);
                WG_COMMIT();
                WG_WAIT(1);
                if (lane == 0) { marrive(BAR(B_ST + 7 + s)); if (s == 2 || s == 6) marrive_rem(mapa(BAR(s == 2 ? B_CR0 : B_CR1), peer)); }
                if (s == 0) { pin(acc); if (wq == 0) TS(37 + wg); gelu16a(acc, 0, vv[0], lo, hi, gy[0], gu[0]); }
                const bool rdy = mtry(BAR(s < 7 ? B_W3 + 9 + s : B_W4));
                if (s == 1) mwait(BAR(B_CRA));
                if (s == 5) mwait(BAR(B_CR0));
                if (s) HSEND(s - 1);
                SCHED_OPEN(ck);
                gelu16b(gy[s & 1], gu[s & 1], Ho[s]);
                if (s < 7) gelu16a(acc, s + 1, vv[(s + 1) & 7], lo, hi, gy[(s + 1) & 1], gu[(s + 1) & 1]);
                SCHED_CLOSE(ck);
                if (!rdy) mwait(BAR(s < 7 ? B_W3 + 9 + s : B_W4));
                if (warp == 0 && (s == 3 || s == 4)) TS(s == 3 ? 65 : 75);
            }
            G4PAIR(0, Ho, 0, 1);
            WG_WAIT(1); pin(acc2);
            if (wq == 0) TS(39 + wg);
            if (lane == 0) marrive(BAR(B_ST + 15));
#pragma unroll
            for (int k = 0; k < 6; k++) vv[k] = lds64(va + 256 + k * 32);
            mwait(BAR(B_CR1));
#define GELU2(k) do { HSEND(7 + (k)); SCHED_OPEN(ck); gelu16a(acc2, k, vv[k], lo, hi, gy[0], gu[0]); gelu16b(gy[0], gu[0], Ho[8 + (k)]); asm volatile("" ::"r"(ck)); cks ^= ck; } while (0)
            uint32_t cks = 0;
            GELU2(0); GELU2(1); GELU2(2);
            mwait(BAR(B_LH0 + wg));
#pragma unroll
            for (int k = 0; k < 8; k++) { uint4 t = lds128(sm + wg * 8192 + HOFF(k) + t128 * 16); Hp[k][0] = t.x; Hp[k][1] = t.y; Hp[k][2] = t.z; Hp[k][3] = t.w; }
            SCHED_FENCE();
            G4PAIR(2, Hp, 0, 0);
            WG_WAIT(1);
            if (lane == 0) marrive(BAR(B_T4));
            GELU2(3); GELU2(4); GELU2(5);
            SCHED_CLOSE(cks);
            if (wq == 0) TS(41 + wg);
            HSEND(13);
            G4PAIR(4, Ho, 8, 0);
        }
        WG_WAIT(1);
        if (lane == 0) marrive(BAR(B_T4 + 1));
        mwait(BAR(B_LH1 + wg));
#pragma unroll
        for (int k = 8; k < 14; k++) { uint4 t = lds128(sm + wg * 8192 + HOFF(k) + t128 * 16); Hp[k][0] = t.x; Hp[k][1] = t.y; Hp[k][2] = t.z; Hp[k][3] = t.w; }
        const int fs = wg ^ hh;
        if (fs) mwait(BAR(B_FA));
        G4PAIR(6, Hp, 8, 0);
        WG_WAIT(1);
        if (!fs && lane == 0) marrive(BAR(B_FA));
        mwait(BAR(B_BS));
        FENCE_ASYNC_G();
        WG_WAIT(0); pin(acc);
        if (wq == 0) TS(43 + fs);
        if (fs && lane == 0) marrive(BAR(B_SA));
        G4PACK();
#define G4HALF(ck, so, h) do { \
            uint2 gv[4]; \
            _Pragma("unroll") for (int q = 0; q < 4; q++) gv[q] = lds64(sm + O_GB + ((ck) & 1) * 256 + c * 8 + (h) * 128 + q * 32); \
            _Pragma("unroll") for (int q = 0; q < 4; q++) \
                stsm4(SWZ(q) + ((so) + (h)) * SLOT, hmul2(po[16 * (h) + 4 * q], hmul2(gv[q].x, rp0)), hmul2(po[16 * (h) + 4 * q + 1], hmul2(gv[q].x, rp1)), \
                      hmul2(po[16 * (h) + 4 * q + 2], hmul2(gv[q].y, rp0)), hmul2(po[16 * (h) + 4 * q + 3], hmul2(gv[q].y, rp1))); } while (0)
#define G4RED1(ck, so, h) do { \
            FENCE_ASYNC_S(); \
            __syncwarp(); \
            if (elect()) \
                asm volatile("cp.reduce.async.bulk.tensor.2d.global.shared::cta.add.tile.bulk_group [%0, {%2, %3}], [%1];" \
                             ::"l"(&tmO), "r"(sm + ((so) + (h)) * SLOT + warp * 2048), "r"(128 * (ck) + 64 * (h)), "r"(128 * (b >> 3) + 16 * warp) : "memory"); } while (0)
        G4HALF(gg ^ 1, 4, 0); G4RED1(gg ^ 1, 4, 0);
        if (fs) {
            G4HALF(gg ^ 1, 4, 1); G4RED1(gg ^ 1, 4, 1);
            if (wq == 0) TS(74);
            mwait(BAR(B_FB));
        }
        G4PAIR(8, Ho, 0, 1);
        G4PAIR(10, Hp, 0, 0);
        G4PAIR(12, Ho, 8, 0);
        if (!fs) G4HALF(gg ^ 1, 4, 1);
        G4PAIR(14, Hp, 8, 0);
        if (!fs) { if (lane == 0) marrive(BAR(B_FB)); G4RED1(gg ^ 1, 4, 1); if (wq == 0) TS(73); }
        mwait(BAR(B_SA));
#pragma unroll
        for (int q = 0; q < 8; q++) {
            const uint2 gv = lds64(sm + O_GB + (gg & 1) * 256 + c * 8 + q * 32);
            po[4 * q] = hmul2(gv.x, rp0); po[4 * q + 1] = hmul2(gv.x, rp1); po[4 * q + 2] = hmul2(gv.y, rp0); po[4 * q + 3] = hmul2(gv.y, rp1);
        }
        SCHED_FENCE();
        WG_WAIT(0); pin(acc);
        if (wq == 0) TS(45 + fs);
#pragma unroll
        for (int q = 0; q < 8; q++) {
            stsm4(SWZ(q & 3) + (8 + (q >> 2)) * SLOT, hmul2(po[4 * q], pk(acc[8 * q], acc[8 * q + 1])), hmul2(po[4 * q + 1], pk(acc[8 * q + 2], acc[8 * q + 3])),
                  hmul2(po[4 * q + 2], pk(acc[8 * q + 4], acc[8 * q + 5])), hmul2(po[4 * q + 3], pk(acc[8 * q + 6], acc[8 * q + 7])));
            if ((q & 3) == 3) G4RED1(gg, 8, q >> 2);
        }
        asm volatile("cp.async.bulk.commit_group;" ::: "memory");
        if (wq == 0) TS(47 + wg);
        asm volatile("cp.async.bulk.wait_group.read 0;" ::: "memory");
        if (fs && wq == 0) TS(51);
        WARRIVE(B_DONE);
    } else {
        unsigned ep;
        {
            const int rg = ba >> 4, cg = ba & 15;
            if (elect()) {
                const int cnt = wq < 2 ? 1 : 8;
#pragma unroll
                for (int i = 0; i < 32; i++) asm volatile("mbarrier.init.shared::cta.b64 [%0], %1;" ::"r"(BAR(32 * wq) + 8 * i), "r"((i >= 8 && wq == 3) ? 4 : cnt) : "memory");
                asm volatile("fence.mbarrier_init.release.cluster;" ::: "memory");
            }
            __syncwarp();
            if (wq < 2) {
                const int i = t128;
                const int tx = i < B_W2 ? 16384 : i < B_LH1 ? ((i >= B_W4 && (i & 2)) ? 24576 : 32768) : i < B_W1 ? 12288 : i < B_J ? 65536 : i == B_J ? (ba < 96 ? 32768 : 24576) : 8192;
                asm volatile("mbarrier.arrive.expect_tx.shared::cta.b64 _, [%0], %1;" ::"r"(BAR(i)), "r"(tx) : "memory");
            }
            __syncwarp();
            if (elect()) {
                if (wq == 1) tma2d(sm + O_T0, &tmM, 64 * cg, 64 * rg, BAR(B_J0));
                else if (wq == 3) asm volatile("prefetch.tensormap [%0];" ::"l"(&tmX) : "memory");
            }
            const unsigned short cr = ldg16(P.c + (64 * rg + (t128 & 63)));
            ep = ld_rlx(P.s->epoch + (ba * 32 + lane));
            asm volatile("barrier.cluster.arrive.relaxed.aligned;" ::: "memory");
            if (wq == 0) TS(77);
            if ((sm & 0xffffffu) != SM_BASE) __trap();
            unsigned* const dm = P.s->modp + (rg * 3072 + 64 * cg + 16 * wq + g + 8 * (c & 1));
            unsigned* const dc = P.s->csum + ((ba & 7) * 1792 + 64 * (ba >> 3) + 16 * wq + g + 8 * (c & 1));
            unsigned* const df = P.s->modf + ((wq - 1) * 512 + 4 * ba + (lane >> 3));
            if (c < 2) {
                st_rlx(dm, 0); st_rlx(dm + 1024, 0); st_rlx(dm + 2048, 0); st_rlx(dc, 0);
                if (ba < 96) st_rlx(dc + 1024, 0);
            }
            if (wq && (lane & 7) == 0) st_rlx(df, 0);
            if (wq < 2) stg128(P.s->hl + ((tau * 4 + gg) * 64 + t128), make_uint4(0, 0, 0, 0));
            const CUtensorMap* jm = &tmM + (lane >= 2);
            const int jc0 = lane < 2 ? 1024 * (lane + 1) + 64 * cg : 64 * (ba >> 3) + 1024 * (lane - 2), jc1 = 64 * (lane < 2 ? rg : ba & 7);
            const bool jon = wq == 3 && lane < (ba < 96 ? 4 : 3);
            SCHED_FENCE();
            asm volatile("barrier.cluster.wait.aligned;" ::: "memory");
            asm volatile("add.u32 %0, %0, 1;" : "+r"(ep));
            const unsigned tag = (ep & 0x7fu) | 0x80u;
            {
                const float v = b2f(cr);
                const bf16 o = __float2bfloat16_rn(wq < 2 ? __fdividef(v, 1.f + __expf(-v)) : 1.f);
                *(bf16*)(smem_raw + O_SV + t128 * 2) = o; *(bf16*)(smem_raw + O_SV + 256 + ((t128 * 2) ^ 32)) = o;
                FENCE_ASYNC_S();
                nbar(4, 128);
            }
#define JOB_MMA(d, off) _Pragma("unroll") for (int k = 0; k < 4; k++) wgmma_n8(d, mkdesc(0, (off) + k * 2048, 16), mkdesc(0, O_SV + k * 32, 16), k)
#define JOB_OUT(dst, d, col) red_xor(dst, ((__float_as_uint(c ? d[2 + (col)] : d[col]) + 0x80u) & 0xffffff00u) | tag)
            {
                mwaitb(BAR(B_J0));
                float d[4];
                WG_FENCE(); JOB_MMA(d, O_T0); WG_COMMIT();
                if (jon) asm volatile("cp.async.bulk.prefetch.tensor.2d.L2.global [%0, {%1,%2}];" ::"l"(jm), "r"(jc0), "r"(jc1) : "memory");
                __syncwarp();
                if (elect()) l2_prefetch(P.w1 + (ba * 2048 + wq * 512), 1024);
                WG_WAIT(0); pin(d);
                if (c < 2) JOB_OUT(dm, d, 0);
                if (wq == 0) TS(78);
            }
            if (wq >= 2) {
                mwaitb(BAR(B_XL + wq - 2));
                if (wq == 3) TS(81);
                const uint32_t a = sm + O_XG + (wq - 2) * 16384 + p * 8192;
                if (elect()) asm volatile("cp.async.bulk.shared::cluster.shared::cta.mbarrier::complete_tx::bytes [%0], [%1], 8192, [%2];"
                                          ::"r"(mapa(a, p ^ 1)), "r"(a), "r"(mapa(BAR(B_XG + wq - 2), p ^ 1)) : "memory");
            }
#pragma unroll 1
            for (int j = 0; j < 2; j++) {
                if (j || wq < 2) {
                    const int sg = 2 * j + wq, cn = 4 * ba + (lane >> 3);
                    float v = __uint_as_float(pollb(P.s->modp + ((lane & 7) * 3072 + sg * 512 + cn), tag, 0xffu) & 0xffffff00u);
                    v += __shfl_xor_sync(~0u, v, 1); v += __shfl_xor_sync(~0u, v, 2); v += __shfl_xor_sync(~0u, v, 4);
                    uint32_t o = pk(rbf(v) + ((sg == 1 || sg == 4) ? 1.f : 0.f), 0.f);
                    if (sg == 4 && o == 0) o = 0x3080;
                    if (sg != 3 && sg != 5) *(unsigned short*)(smem_raw + O_ML + (sg == 4 ? 3 : sg) * 8 + (lane >> 3) * 2) = (unsigned short)o;
                    if (sg >= 3 && (lane & 7) == 0) red_xor(df, (o << 16) | tag);
                    if (wq == 0) TS(54 + j);
                }
                WARRIVE(B_MOD0 + j);
                if (j) break;
                mwaitb(BAR(B_KP));
                {
                    const uint32_t k0 = sm + wq * KST_W + (lane & 15) * (2 * KP_P), ft = sm + O_FT + wq * FT_CH + 64 + lane * 8;
                    const uint32_t a2 = k0 + (12 + 2 * (lane >> 4)) * 4, a3 = k0 + (16 + (lane >> 4)) * 4, nx = (lane & 15) == 15 ? 4 - 30 * KP_P : 2 * KP_P;
#pragma unroll 1
                    for (int h = 0; h < 2; h++) {
                        const uint32_t o[4] = {h ? a3 + nx : a2 + 4, h ? a3 + nx + 8 : a2 + KP_P, h ? a3 + KP_P : a2 + KP_P + 4, h ? a3 + KP_P + 8 : a2 + nx + ((lane & 15) == 15 ? 4 : 0)};
                        float v[4];
#pragma unroll
                        for (int it = 0; it < 4; it++) v[it] = ldsf(o[it]) + ldsf(o[it] + 4 * KST_W);
#pragma unroll
                        for (int it = 0; it < 4; it++) {
                            const bool cont = h && (it & 1);
                            const float pv = __shfl_sync(~0u, lane == 31 ? (cont ? v[it & 2] : 0.f) : v[it], lane - 1);
                            const uint32_t d = ft + (h ? 1792 + (it >> 1) * 576 + (it & 1) * 256 : it * 448), t = pk(v[it], pv);
                            sts32(d, t);
                            if (!cont || lane < 24) sts32(d + 68, t);
                            if (!h && lane == 31) {
                                const uint32_t u = t << 16;
                                sts32(d + 8, u); sts32(d + 76, u);
                                if (it == 3) { const uint32_t e = ft + 2944 - 248; sts32(e, t & 0xffffu); sts32(e + 68, t & 0xffffu); sts32(e + 8, u); sts32(e + 76, u); }
                            }
                        }
                    }
                }
                if (wq == 0) TS(56);
                mwaitb(BAR(B_TAB));
                if (jon) tma2d(sm + O_T1 + lane * T_STRIDE, jm, jc0, jc1, BAR(B_J));
                __syncwarp();
                if (elect()) { l2_prefetch(P.w2 + (ba * 2048 + wq * 512), 1024); l2_prefetch(P.w4 + (ba * 7168 + wq * 1792), 3584); }
                {
                    mwaitb(BAR(B_XD));
                    if (wq == 0) TS(57);
                    const uint32_t ub = sm + O_U + wq * U_CH + 112 + (lane >> 1) * 16, bo = sm + O_BOX + wq * BOX_CH;
                    const int hf = lane & 1;
                    if (lane < 3) sts128(bo + (lane == 2 ? B9_O + H3O : lane * 3200 + H2O), 0, 0, 0, 0);
#pragma unroll 1
                    for (int it = 0; it < 6; it++) {
                        const uint2 u0 = lds64(ub + it * 256 + hf * U_H + 8);
                        const uint4 u1 = lds128(ub + it * 256 + (hf ? 16 : U_H)), u2 = lds128(ub + it * 256 + hf * U_H + 16);
                        const uint32_t E[9] = {u0.x, u0.y, u1.x, u1.y, u1.z, u1.w, u2.x, u2.y, u2.z};
                        uint32_t O[8], A[8], F[6];
#pragma unroll
                        for (int k = 0; k < 8; k++) { O[k] = __byte_perm(E[k], E[k + 1], 0x5432); A[k] = hadd2(E[k], O[k]); }
#pragma unroll
                        for (int k = 0; k < 6; k++) F[k] = hadd2(A[k], A[k + 1]);
                        const uint32_t o2 = bo + hf * H2O + (16 * it + (lane >> 1) + 1) * 16, o3 = o2 - hf * (H2O - H3O);
                        sts128(o2 + B5_O, hadd2(F[1], E[3]), hadd2(F[2], E[4]), hadd2(F[3], E[5]), hadd2(F[4], E[6]));
                        sts128(o2 + B3_O, hadd2(O[3], A[4]), hadd2(O[4], A[5]), hadd2(O[5], A[6]), hadd2(O[6], A[7]));
                        if (it < 4) {
                            sts128(o3 + B9_O, hadd2(F[0], hadd2(F[2], E[4])), hadd2(F[1], hadd2(F[3], E[5])), hadd2(F[2], hadd2(F[4], E[6])), hadd2(F[3], hadd2(F[5], E[7])));
                            sts128(o3 + B7_O, hadd2(hadd2(O[0], A[1]), F[2]), hadd2(hadd2(O[1], A[2]), F[3]), hadd2(hadd2(O[2], A[3]), F[4]), hadd2(hadd2(O[3], A[4]), F[5]));
                            sts128(o3 + B2_O, A[4], A[5], A[6], A[7]);
                        }
                        if (it == 1) {
                        WARRIVE(B_FAR);
                {
                    mwaitb(BAR(B_J));
                    if (wq == 0) TS(79);
                    float d[4][4];
                    WG_FENCE();
#pragma unroll
                    for (int i = 0; i < 4; i++) { JOB_MMA(d[i], O_T1 + i * T_STRIDE); }
                    WG_COMMIT();
                    WG_WAIT(0);
#pragma unroll
                    for (int i = 0; i < 4; i++) pin(d[i]);
                    nbar(4, 128);
                    if (elect()) {
                        tma2d(sm + wq * SLOT, &tmW1, 128 * gg, 128 * wq, BAR(B_W1));
                        if (wq < 3) tma2d(sm + (4 + wq) * SLOT, &tmW1, 128 * gg + 64, 128 * wq, BAR(B_W1 + 1));
                        asm volatile("prefetch.tensormap [%0];" ::"l"(wq ? &tmW1 + wq : &tmO) : "memory"); asm volatile("prefetch.tensormap [%0];" ::"l"(&tmW4 + wq) : "memory");
                    }
                    if (c < 2) {
                        JOB_OUT(dm + 1024, d[0], 0); JOB_OUT(dm + 2048, d[1], 0); JOB_OUT(dc, d[2], 1);
                        if (ba < 96) JOB_OUT(dc + 1024, d[3], 1);
                    }
                    if (wq == 0) TS(80);
                }
                        }
                    }
                    WARRIVE(B_FAR + 1);
                    if (wq == 0) TS(58);
                }
            }
            if (wq == 0) TS(60);
        }
        asm volatile("setmaxnreg.dec.sync.aligned.u32 40;");
        if (wq >= 2) {
            unsigned* f = P.s->f0;
            uint32_t d = sm + O_A + p * 32768, fb = BAR(B_HF + 4 * p), c0 = 64 * tau, c1 = 256 * p;
            const CUtensorMap* m = &tmXS;
            asm volatile("" : "+r"(d), "+r"(fb), "+r"(c0), "+r"(c1), "+l"(m), "+l"(f));
            SCHED_FENCE();
            mwaitb(BAR(B_CEND));
            if (wq == 3) { if (elect()) tma2d(sm + 7 * SLOT, &tmW1, 128 * gg + 64, 384, BAR(B_W1 + 1)); }
            else {
                if (elect()) publish(f);
                TS(19);
                poll(f, 128 * ep);
                TS(21);
                FENCE_ASYNC_G();
#pragma unroll
                for (int q = 0; q < 4; q++) {
                    if (q >= 2) mwait(fb + 8 * (q - 2));
                    if (elect()) tma2d_mc(d + q * 8192, m, c0, c1 + 64 * q, fb + 8 * q);
                }
            }
        }
        else {
            mwait(BAR(B_BT));
            float4 gs = ldsf4(sm + O_GC + c * 16); float g4 = ldsf(sm + O_GC + 64 + c * 4);
            gs.x = qsum(gs.x); gs.y = qsum(gs.y); gs.z = qsum(gs.z); gs.w = qsum(gs.w); g4 = qsum(g4);
            SCHED_FENCE();
            const uint32_t a = sm + O_RP + t128 * 32;
            mwait(BAR(B_RP));
            const float4 t = ldsf4(a), u = ldsf4(a + 2048);
            const float2 t2 = ldsf2(a + 16), u2 = ldsf2(a + 2064);
            float m1, r1, m2, r2;
            row_stats(t.x + u.x, t2.x + u2.x, m1, r1);
            row_stats(fmaf(r1, fmaf(-m1, gs.x, t.y + u.y), gs.y),
                      fmaf(r1, fmaf(r1, fmaf(m1, fmaf(m1, gs.z, -2.f * (t.z + u.z)), t2.y + u2.y), 2.f * fmaf(-m1, gs.w, t.w + u.w)), g4), m2, r2);
            r2 *= GK0;
            const uint32_t pz = pk(-r2 * m2, r1);
            sts128(sm + O_RC + t128 * 16, __float_as_uint(r1 * r2), pk(-r1 * r2 * m1, r2), pz, pk(-m1 * bhi(pz), 0.f));
            WARRIVE_N(B_RC, 2);
            if (wq == 0) TS(24);
#pragma unroll 1
            for (int h = 0; h < 2; h++) {
            const int i = min(t128 + 64 * h, 111);
            const unsigned* s = P.s->csum + (224 * fj + 2 * i);
            unsigned t[8][2], bad;
            do {
                bad = 0;
#pragma unroll
                for (int r = 0; r < 8; r++) asm volatile("ld.relaxed.gpu.global.v2.u32 {%0,%1}, [%2];" : "=r"(t[r][0]), "=r"(t[r][1]) : "l"(s + r * 1792) : "memory");
#pragma unroll
                for (int r = 0; r < 8; r++) bad |= (t[r][0] ^ (ep | 0x80u)) | (t[r][1] ^ (ep | 0x80u));
            } while (__any_sync(~0u, bad & 0xffu));
            float a0 = 0.f, a1 = 0.f;
#pragma unroll
            for (int r = 0; r < 8; r++) { a0 += __uint_as_float(t[r][0] & 0xffffff00u); a1 += __uint_as_float(t[r][1] & 0xffffff00u); }
            sts32(sm + O_V4 + (i >> 3) * 32 + (i & 3) * 8 + (i & 4), pk(a0, a1));
        }
        if (wq == 0) TS(76);
            WARRIVE_N(B_V4, 2);
            {
                const int tn = tau + ((gg & 1) ? 1 : -1);
                uint32_t d[8] = {0, 0, 0, 0, 0, 0, 0, 0};
                mwait(BAR(B_PH));
                if ((unsigned)tn < 32u) {
                    const uint4* hp = P.s->hl + ((tn * 4 + (gg ^ (2 * wq))) * 64 + 2 * lane);
                    do {
                        asm volatile("{\n.reg .b64 a, b, c, d;\nld.relaxed.gpu.global.v2.b64 {a, b}, [%8];\nld.relaxed.gpu.global.v2.b64 {c, d}, [%8+16];\n"
                                     "mov.b64 {%0, %1}, a;\nmov.b64 {%2, %3}, b;\nmov.b64 {%4, %5}, c;\nmov.b64 {%6, %7}, d;\n}"
                                     : "=r"(d[0]), "=r"(d[1]), "=r"(d[2]), "=r"(d[3]), "=r"(d[4]), "=r"(d[5]), "=r"(d[6]), "=r"(d[7]) : "l"(hp) : "memory");
                    } while (__any_sync(~0u, ((d[1] ^ ep) | (d[3] ^ ep) | (d[5] ^ ep) | (d[7] ^ ep)) != 0));
                }
                sts128(sm + O_HB + t128 * 16, d[0], d[2], d[4], d[6]);
                WARRIVE_N(B_HB, 2);
            }
        }
        if (wq == 0) {
            mwait(BAR(B_V4)); mwait(BAR(B_HD)); mwait<1>(BAR(B_HF + 6 + p));
#pragma unroll 1
            for (int i = 0; i < 16; i++) {
                uint32_t d = sm + W3A(i), c0 = 224 * fj + (i >> 3) * 128, c1 = 128 * ZG((i >> 1) & 3) + 64 * (i & 1);
                const CUtensorMap* m = &tmW3 + (i >> 3);
                asm volatile("" : "+r"(d), "+r"(c0), "+r"(c1), "+l"(m));
                SCHED_FENCE();
                mwait(BAR(B_E2 + ((0xDDCBA98765410000ull >> (4 * i)) & 15)));
                if (elect()) tma3d(d, m, c0, c1, 0, BAR(B_W3 + i));
            }
            P.s->epoch[ba * 32 + lane] = ep;
        } else if (wq == 1) {
            if (lane < 4) asm volatile("mbarrier.arrive.expect_tx.shared::cta.b64 _, [%0], 8192;" ::"r"(BAR(B_HF + 4 + lane)) : "memory");
            {
                uint32_t d = sm + O_A + 2 * SLOT + p * 8192, fb = BAR(B_HF + 4 + p), c0 = 128 * ZG(2) + 64 * p, c1 = 64 * tau + ((gg & 1) ? 1 : 3), c2 = 64 * tau + ((gg & 1) ? 0 : 4);
                const CUtensorMap* m = &tmH;
                asm volatile("" : "+r"(d), "+r"(fb), "+r"(c0), "+r"(c1), "+r"(c2), "+l"(m));
                SCHED_FENCE();
                poll(P.s->fh + min(max(tau + ((lane & 1) ? 0 : (gg & 1) ? -1 : 1), 0), 31) * 32, 4 * ep);
                TS(84);
                FENCE_ASYNC_G();
                if (elect()) tma2d_mc(d, m, c0, c1, fb);
                if (elect()) tma2d_mc(d + SLOT, m, c0 + 256, c2, fb + 16);
            }
            {
                uint32_t a = sm + (2 * p + hh) * SLOT, ra = mapa(a, p ^ 1), rb = mapa(BAR(B_ZF + 2 * p + hh), p ^ 1);
                uint32_t d = sm + (hh ^ 1) * SLOT + p * 8192, fb = BAR(B_ZF + (hh ^ 1));
                const uint4* zp = P.s->z + ((tau ^ 1) * 8 + 2 * (gg & 1) + p) * 512;
                asm volatile("" : "+r"(a), "+r"(ra), "+r"(rb), "+r"(d), "+r"(fb), "+l"(zp));
                SCHED_FENCE();
                mwait(BAR(B_ZL)); mwait(BAR(B_PZP));
                if (elect()) asm volatile("cp.async.bulk.shared::cluster.shared::cta.mbarrier::complete_tx::bytes [%0], [%1], 16384, [%2];" ::"r"(ra), "r"(a), "r"(rb) : "memory");
                poll(P.s->fz + (b >> 3) * 32, 8 * ep);
                TS(86);
                FENCE_ASYNC_G();
                if (elect()) bulk_ld_mc(d, zp, 8192, fb);
                if (elect()) bulk_ld_mc(d + 2 * SLOT, zp + 2048, 8192, fb + 16);
#pragma unroll 1
                for (int u = 2; u < 4; u++) {
                    const uint4* z2 = P.s->z + ((tau & ~1) * 8 + 2 * ZG(u) + p) * 512;
                    uint32_t d2 = sm + 2 * u * SLOT + p * 8192, f2 = BAR(B_ZF + 2 * u);
                    asm volatile("" : "+r"(d2), "+r"(f2), "+l"(z2));
                    SCHED_FENCE();
                    mwait(fb);
                    if (elect()) bulk_ld_mc(d2, z2, 8192, f2);
                    if (elect()) bulk_ld_mc(d2 + SLOT, z2 + 4096, 8192, f2 + 8);
                    fb = f2;
                }
            }
#pragma unroll 1
            for (int j = 0; j < 8; j++) {
                const int k0 = 224 * (fj ^ (j & 1)) + 64 * (j & 2), pn = 2 * (gg ^ 1 ^ (j >> 2)), sl = (int)(W4SLOT >> (8 * j));
                mwait(BAR(B_ST + 10 + ((0x76655420 >> (4 * j)) & 15)));
                if (elect()) tma3d(sm + (sl & 15) * SLOT, &tmW4, 0, k0, pn, BAR(B_W4 + j));
                if (j < 2) mwait(BAR(B_ST + 11 + 2 * j));
                if (elect()) tma3d(sm + ((sl >> 4) & 15) * SLOT, &tmW4 + ((j >> 1) & 1), 0, k0 + 64, pn, BAR(B_W4 + j));
            }
        } else {
            if (wq == 2) {
#pragma unroll 1
                for (int i = 0; i < 8; i++) {
                    const int pn = i & 1, sl = (i >> 1) ^ (2 * pn);
                    mwait(BAR(B_E1 + i));
                    if (elect()) tma2d(sm + (4 * pn + sl) * SLOT, &tmW2, 128 * gg + 64 * pn, 128 * (i < 4 ? gg ^ (i & 2) : ZG(i >> 1)), BAR(B_W2 + (i >> 1)));
                }
                mwait(BAR(B_PH));
                if (elect()) asm volatile("mbarrier.arrive.shared::cluster.b64 _, [%0], 4;" ::"r"(mapa(BAR(B_PHP), p ^ 1)) : "memory");
                mwait(BAR(B_PHP));
                if (elect()) asm volatile("cp.async.bulk.shared::cluster.shared::cta.mbarrier::complete_tx::bytes [%0], [%1], 16384, [%2];"
                                          ::"r"(mapa(sm + O_A, p ^ 1)), "r"(sm + 12 * SLOT), "r"(mapa(BAR(B_HP), p ^ 1)) : "memory");
            }
            unsigned* f = wq == 3 ? P.s->fh + tau * 32 : P.s->fz + (b >> 3) * 32;
            asm volatile("" : "+l"(f));
            SCHED_FENCE();
            mwaitb(BAR(B_PH + 3 - wq));
            if (elect()) publish(f);
            TS(88 + wq - 2);
            if (wq == 2) {
                mwait(BAR(B_BA)); mwait(BAR(B_ZF + 4 + (hh ^ 1)));
                unsigned* fb = P.s->fb + (2 * (b >> 3) + p) * 32;
                if (elect()) {
#pragma unroll 1
                    for (int i = 0; i < 8; i++)
                        asm volatile("cp.async.bulk.tensor.2d.global.shared::cta.tile.bulk_group [%0, {%2, %3}], [%1];"
                                     ::"l"(&tmO), "r"(sm + 11 * SLOT + i * 2048), "r"(128 * gg + 64 * (i >> 2)), "r"(64 * tau + 16 * (i & 3)) : "memory");
                    asm volatile("cp.async.bulk.commit_group;\ncp.async.bulk.wait_group.read 0;" ::: "memory");
                    asm volatile("mbarrier.arrive.shared::cluster.b64 _, [%0], 4;" ::"r"(mapa(BAR(B_CRA), p ^ 1)) : "memory");
                    asm volatile("cp.async.bulk.wait_group 0;" ::: "memory");
                    FENCE_ASYNC_G();
                    publish(fb);
                }
                TS(90);
                poll(fb, 4 * ep);
                WARRIVE_N(B_BS, 4);
                TS(91);
            } else {
                mwaitb(BAR(B_DONE));
            }
        }
    }
}

typedef CUresult (*EncodeFn)(CUtensorMap*, CUtensorMapDataType, cuuint32_t, void*, const cuuint64_t*, const cuuint64_t*, const cuuint32_t*,
                             const cuuint32_t*, CUtensorMapInterleave, CUtensorMapSwizzle, CUtensorMapL2promotion, CUtensorMapFloatOOBfill);

static void make_map(EncodeFn enc, CUtensorMap* m, const void* base, int rank, const cuuint64_t* dims, const cuuint64_t* strides,
                     const cuuint32_t* box, CUtensorMapSwizzle sw) {
    cuuint32_t es[3] = {1, 1, 1};
    enc(m, CU_TENSOR_MAP_DATA_TYPE_BFLOAT16, rank, (void*)base, dims, strides, box, es, CU_TENSOR_MAP_INTERLEAVE_NONE, sw,
        CU_TENSOR_MAP_L2_PROMOTION_L2_128B, CU_TENSOR_MAP_FLOAT_OOB_FILL_NONE);
}

extern "C" void kernel_launch(void* const* d_in, const int* in_sizes, int n_in, void* d_out, int out_size) {
    Params P;
    P.x = (const bf16*)d_in[0];
    for (int i = 0; i < 8; i++) P.par[i] = (const bf16*)d_in[1 + i];
    P.w1 = (const bf16*)d_in[10]; P.w2 = (const bf16*)d_in[11]; P.w3 = (const bf16*)d_in[12];
    P.w4 = (const bf16*)d_in[13]; P.c = (const bf16*)d_in[14]; P.wmod = (const bf16*)d_in[15]; P.out = (bf16*)d_out;

    void* fn = nullptr; cudaDriverEntryPointQueryResult qr;
    cudaGetDriverEntryPoint("cuTensorMapEncodeTiled", &fn, cudaEnableDefault, &qr);
    EncodeFn enc = (EncodeFn)fn;
    void* hbuf = nullptr; cudaGetSymbolAddress(&hbuf, g_s);
    P.s = (Scratch*)hbuf;
    Maps M;
    { cuuint64_t d[3] = {512, 256, 8}, s[2] = {8192, 1024}; cuuint32_t bx[3] = {8, 128, 4}; make_map(enc, &tmX, P.x, 3, d, s, bx, CU_TENSOR_MAP_SWIZZLE_NONE); }
    { cuuint64_t d[2] = {512, 512}, s[1] = {1024}; cuuint32_t bx[2] = {64, 128};
      make_map(enc, &tmW1, P.w1, 2, d, s, bx, CU_TENSOR_MAP_SWIZZLE_128B); make_map(enc, &tmW2, P.w2, 2, d, s, bx, CU_TENSOR_MAP_SWIZZLE_128B); }
    { cuuint64_t d[3] = {1792, 512, 2}, s[2] = {3584, 128}, sb[2] = {3584, 64}; cuuint32_t bx[3] = {64, 64, 2};
      make_map(enc, &tmW3, P.w3, 3, d, s, bx, CU_TENSOR_MAP_SWIZZLE_128B); make_map(enc, &tmW3b, P.w3, 3, d, sb, bx, CU_TENSOR_MAP_SWIZZLE_128B); }
    { cuuint64_t d[3] = {64, 1792, 8}, s[2] = {1024, 128}; cuuint32_t bx[3] = {64, 64, 2}, bh[3] = {64, 32, 2};
      make_map(enc, &tmW4, P.w4, 3, d, s, bx, CU_TENSOR_MAP_SWIZZLE_128B); make_map(enc, &tmW4h, P.w4, 3, d, s, bh, CU_TENSOR_MAP_SWIZZLE_128B); }
    for (int i = 0; i < 4; i++) {
        cuuint64_t w = i == 0 ? 512 : i == 1 ? 2048 : i == 2 ? 3072 : 1792, d[2] = {w, i == 0 ? 2052u : 512u}, s[1] = {2 * w}; cuuint32_t bx[2] = {64, 64};
        make_map(enc, &tmH + i, i == 0 ? P.s->h : i == 1 ? P.s->xs : i == 2 ? P.wmod : P.w3, 2, d, s, bx, CU_TENSOR_MAP_SWIZZLE_128B);
    }
    { cuuint64_t d[2] = {512, 2048}, s[1] = {1024}; cuuint32_t bx[2] = {64, 16}; make_map(enc, &tmO, P.out, 2, d, s, bx, CU_TENSOR_MAP_SWIZZLE_128B); }
    cudaFuncSetAttribute(fused_kernel, cudaFuncAttributeMaxDynamicSharedMemorySize, SMEM_BYTES);
    fused_kernel<<<128, 384, SMEM_BYTES, cudaStreamPerThread>>>(P, M);
}
```
